```python
import torch

def _softmax(x, axis=-1):
    return torch.softmax(x, dim=axis)
def _gelu(x):
    return torch.nn.functional.gelu(x, approximate="tanh")
def _silu(x):
    return torch.nn.functional.silu(x)
def _sigmoid(x):
    return torch.sigmoid(x)
def _layernorm(x, axis=-1, eps=1e-5):
    m = x.mean(dim=axis, keepdim=True)
    v = x.var(dim=axis, keepdim=True, unbiased=False)
    return (x - m) / torch.sqrt(v + eps)
def _scatter_add(tgt, idx, src, axis=0):
    return tgt.clone().index_add_(axis, idx, src)
def _segment_sum(src, seg, n):
    out = torch.zeros((n,) + src.shape[1:], dtype=src.dtype)
    return out.index_add_(0, seg, src)
def _pad(x, pw):
    flat = tuple(v for pair in reversed(pw) for v in pair)
    return torch.nn.functional.pad(x, flat)

kernel_name = 'concat_heads__grouped_kv_mqa__spectral_gfnet__prompt'

def setup_inputs():

    _w = (lambda a: (lambda t: t.to(torch.bfloat16) if t.is_floating_point() else t)(torch.as_tensor(a)))
    def _A_setup():
        B, S, D, H = 1, 2048, 448, 16
        Dh = D // H
        return {
            "x": _w((lambda *s: torch.randn(*s, dtype=torch.bfloat16) * 0.05)(B, S, D)),
            "wq": _w((lambda *s: torch.randn(*s, dtype=torch.bfloat16) * 0.8)(D, H * Dh)),
            "wk": _w((lambda *s: torch.randn(*s, dtype=torch.bfloat16) * 0.8)(D, Dh)),
            "wv": _w((lambda *s: torch.randn(*s, dtype=torch.bfloat16) * 0.05)(D, Dh)),
            "wo": _w((lambda *s: torch.randn(*s, dtype=torch.bfloat16) * 0.05)(H * Dh, D)),
        }
    _A_in = _A_setup()

    def _B_setup():
        B, S, D = 1, 2048, 448
        Df = D // 2 + 1
        return {
            "x": _w((lambda *s: torch.randn(*s, dtype=torch.bfloat16) * 0.05)(B, S, D)),
            "w_r": _w((lambda *s: torch.randn(*s, dtype=torch.bfloat16) * 0.4)(S, Df) * 0.02),
            "w_i": _w((lambda *s: torch.randn(*s, dtype=torch.bfloat16) * 0.4)(S, Df) * 0.02),
        }
    _B_in = _B_setup()

    return {
        "A_x": _A_in["x"],
        "A_wq": _A_in["wq"],
        "A_wk": _A_in["wk"],
        "A_wv": _A_in["wv"],
        "A_wo": _A_in["wo"],
        "B_x": _B_in["x"],
        "B_w_r": _B_in["w_r"],
        "B_w_i": _B_in["w_i"],
    }

def reference(A_x, A_wq, A_wk, A_wv, A_wo, B_x, B_w_r, B_w_i):
    def _A_ref(x, wq, wk, wv, wo):
        B, S, D = x.shape
        H = 16
        Dh = D // H
        q = (lambda x, *d: x.permute(*d))((x @ wq).reshape(B, S, H, Dh), 0, 2, 1, 3)
        k = x @ wk
        v = x @ wv
        scores = torch.einsum("bhqd,bkd->bhqk", q, k) * (Dh ** -0.5)
        p = _softmax(scores, axis=-1)
        o = torch.einsum("bhqk,bkd->bhqd", p, v)
        return (lambda x, *d: x.permute(*d))(o, 0, 2, 1, 3).reshape(B, S, H * Dh) @ wo

    def _B_ref(x, w_r, w_i):
        B, S, D = x.shape
        X = (lambda x, axes=(-2,-1): torch.fft.rfft2(x.float(), dim=axes))(x, axes=(-2, -1))
        W = w_r + 1j * w_i
        X = X * W
        y = (lambda x, s, axes=(-2,-1): torch.fft.irfft2(x, s=s, dim=axes).to(torch.bfloat16))(X, (S, D), axes=(-2, -1))
        return y

    a = _A_ref(A_x, A_wq, A_wk, A_wv, A_wo)
    b = _B_ref(B_x, B_w_r, B_w_i)
    return torch.concatenate([a, b], axis=-1)
```

```cpp
#include <cuda_runtime.h>
#include <cuda.h>
#include <cuda_bf16.h>
#include <stdint.h>

#define SEQ 2048
#define DM 448
#define NHEAD 16
#define DHEAD 28
#define DF 225
#define OUT_LD 896

__device__ const float2 TWA2048[2048] = {
{1.0e+00f,0.0e+00f},{1.0e+00f,0.0e+00f},{1.0e+00f,0.0e+00f},{1.0e+00f,0.0e+00f},
{1.0e+00f,0.0e+00f},{1.0e+00f,0.0e+00f},{1.0e+00f,0.0e+00f},{1.0e+00f,0.0e+00f},
{1.0e+00f,0.0e+00f},{1.0e+00f,0.0e+00f},{1.0e+00f,0.0e+00f},{1.0e+00f,0.0e+00f},
{1.0e+00f,0.0e+00f},{1.0e+00f,0.0e+00f},{1.0e+00f,0.0e+00f},{1.0e+00f,0.0e+00f},
{1.0e+00f,0.0e+00f},{1.0e+00f,0.0e+00f},{1.0e+00f,0.0e+00f},{1.0e+00f,0.0e+00f},
{1.0e+00f,0.0e+00f},{1.0e+00f,0.0e+00f},{1.0e+00f,0.0e+00f},{1.0e+00f,0.0e+00f},
{1.0e+00f,0.0e+00f},{1.0e+00f,0.0e+00f},{1.0e+00f,0.0e+00f},{1.0e+00f,0.0e+00f},
{1.0e+00f,0.0e+00f},{1.0e+00f,0.0e+00f},{1.0e+00f,0.0e+00f},{1.0e+00f,0.0e+00f},
{1.0e+00f,0.0e+00f},{1.0e+00f,0.0e+00f},{1.0e+00f,0.0e+00f},{1.0e+00f,0.0e+00f},
{1.0e+00f,0.0e+00f},{1.0e+00f,0.0e+00f},{1.0e+00f,0.0e+00f},{1.0e+00f,0.0e+00f},
{1.0e+00f,0.0e+00f},{1.0e+00f,0.0e+00f},{1.0e+00f,0.0e+00f},{1.0e+00f,0.0e+00f},
{1.0e+00f,0.0e+00f},{1.0e+00f,0.0e+00f},{1.0e+00f,0.0e+00f},{1.0e+00f,0.0e+00f},
{1.0e+00f,0.0e+00f},{1.0e+00f,0.0e+00f},{1.0e+00f,0.0e+00f},{1.0e+00f,0.0e+00f},
{1.0e+00f,0.0e+00f},{1.0e+00f,0.0e+00f},{1.0e+00f,0.0e+00f},{1.0e+00f,0.0e+00f},
{1.0e+00f,0.0e+00f},{1.0e+00f,0.0e+00f},{1.0e+00f,0.0e+00f},{1.0e+00f,0.0e+00f},
{1.0e+00f,0.0e+00f},{1.0e+00f,0.0e+00f},{1.0e+00f,0.0e+00f},{1.0e+00f,0.0e+00f},
{1.0e+00f,0.0e+00f},{1.0e+00f,0.0e+00f},{1.0e+00f,0.0e+00f},{1.0e+00f,0.0e+00f},
{1.0e+00f,0.0e+00f},{1.0e+00f,0.0e+00f},{1.0e+00f,0.0e+00f},{1.0e+00f,0.0e+00f},
{1.0e+00f,0.0e+00f},{1.0e+00f,0.0e+00f},{1.0e+00f,0.0e+00f},{1.0e+00f,0.0e+00f},
{1.0e+00f,0.0e+00f},{1.0e+00f,0.0e+00f},{1.0e+00f,0.0e+00f},{1.0e+00f,0.0e+00f},
{1.0e+00f,0.0e+00f},{1.0e+00f,0.0e+00f},{1.0e+00f,0.0e+00f},{1.0e+00f,0.0e+00f},
{1.0e+00f,0.0e+00f},{1.0e+00f,0.0e+00f},{1.0e+00f,0.0e+00f},{1.0e+00f,0.0e+00f},
{1.0e+00f,0.0e+00f},{1.0e+00f,0.0e+00f},{1.0e+00f,0.0e+00f},{1.0e+00f,0.0e+00f},
{1.0e+00f,0.0e+00f},{1.0e+00f,0.0e+00f},{1.0e+00f,0.0e+00f},{1.0e+00f,0.0e+00f},
{1.0e+00f,0.0e+00f},{1.0e+00f,0.0e+00f},{1.0e+00f,0.0e+00f},{1.0e+00f,0.0e+00f},
{1.0e+00f,0.0e+00f},{1.0e+00f,0.0e+00f},{1.0e+00f,0.0e+00f},{1.0e+00f,0.0e+00f},
{1.0e+00f,0.0e+00f},{1.0e+00f,0.0e+00f},{1.0e+00f,0.0e+00f},{1.0e+00f,0.0e+00f},
{1.0e+00f,0.0e+00f},{1.0e+00f,0.0e+00f},{1.0e+00f,0.0e+00f},{1.0e+00f,0.0e+00f},
{1.0e+00f,0.0e+00f},{1.0e+00f,0.0e+00f},{1.0e+00f,0.0e+00f},{1.0e+00f,0.0e+00f},
{1.0e+00f,0.0e+00f},{1.0e+00f,0.0e+00f},{1.0e+00f,0.0e+00f},{1.0e+00f,0.0e+00f},
{1.0e+00f,0.0e+00f},{1.0e+00f,0.0e+00f},{1.0e+00f,0.0e+00f},{1.0e+00f,0.0e+00f},
{1.0e+00f,0.0e+00f},{1.0e+00f,0.0e+00f},{1.0e+00f,0.0e+00f},{1.0e+00f,0.0e+00f},
{1.0e+00f,0.0e+00f},{9.999953e-01f,-3.0679568e-03f},{9.9998116e-01f,-6.1358847e-03f},{9.999576e-01f,-9.203754e-03f},
{9.999247e-01f,-1.2271538e-02f},{9.9988234e-01f,-1.5339206e-02f},{9.998306e-01f,-1.840673e-02f},{9.997694e-01f,-2.147408e-02f},
{9.996988e-01f,-2.4541229e-02f},{9.996188e-01f,-2.7608145e-02f},{9.995294e-01f,-3.0674804e-02f},{9.994306e-01f,-3.3741172e-02f},
{9.9932235e-01f,-3.6807224e-02f},{9.9920475e-01f,-3.9872926e-02f},{9.9907774e-01f,-4.293826e-02f},{9.989413e-01f,-4.600318e-02f},
{9.9879545e-01f,-4.9067676e-02f},{9.9864024e-01f,-5.2131705e-02f},{9.9847555e-01f,-5.5195246e-02f},{9.9830157e-01f,-5.8258265e-02f},
{9.981181e-01f,-6.1320737e-02f},{9.979253e-01f,-6.438263e-02f},{9.9772304e-01f,-6.744392e-02f},{9.9751145e-01f,-7.0504576e-02f},
{9.9729043e-01f,-7.356457e-02f},{9.9706006e-01f,-7.6623864e-02f},{9.968203e-01f,-7.968244e-02f},{9.965711e-01f,-8.274026e-02f},
{9.963126e-01f,-8.579731e-02f},{9.960447e-01f,-8.885355e-02f},{9.957674e-01f,-9.1908954e-02f},{9.954808e-01f,-9.49635e-02f},
{9.951847e-01f,-9.801714e-02f},{9.948793e-01f,-1.0106986e-01f},{9.945646e-01f,-1.0412163e-01f},{9.9424046e-01f,-1.0717242e-01f},
{9.93907e-01f,-1.10222206e-01f},{9.935641e-01f,-1.1327095e-01f},{9.932119e-01f,-1.1631863e-01f},{9.928504e-01f,-1.19365215e-01f},
{9.9247956e-01f,-1.2241068e-01f},{9.920993e-01f,-1.2545498e-01f},{9.9170977e-01f,-1.284981e-01f},{9.9131083e-01f,-1.3154003e-01f},
{9.9090266e-01f,-1.345807e-01f},{9.904851e-01f,-1.3762012e-01f},{9.900582e-01f,-1.4065824e-01f},{9.89622e-01f,-1.4369503e-01f},
{9.891765e-01f,-1.4673047e-01f},{9.8872167e-01f,-1.4976454e-01f},{9.882576e-01f,-1.5279719e-01f},{9.8778415e-01f,-1.558284e-01f},
{9.873014e-01f,-1.5885815e-01f},{9.868094e-01f,-1.618864e-01f},{9.863081e-01f,-1.6491312e-01f},{9.857975e-01f,-1.6793829e-01f},
{9.8527765e-01f,-1.7096189e-01f},{9.847485e-01f,-1.7398387e-01f},{9.842101e-01f,-1.7700422e-01f},{9.836624e-01f,-1.800229e-01f},
{9.831055e-01f,-1.8303989e-01f},{9.825393e-01f,-1.8605515e-01f},{9.819639e-01f,-1.8906866e-01f},{9.813792e-01f,-1.920804e-01f},
{9.8078525e-01f,-1.9509032e-01f},{9.801821e-01f,-1.980984e-01f},{9.795698e-01f,-2.0110464e-01f},{9.789482e-01f,-2.0410897e-01f},
{9.783174e-01f,-2.0711137e-01f},{9.7767735e-01f,-2.1011184e-01f},{9.7702813e-01f,-2.1311031e-01f},{9.7636974e-01f,-2.161068e-01f},
{9.757021e-01f,-2.1910124e-01f},{9.7502536e-01f,-2.2209363e-01f},{9.7433937e-01f,-2.2508392e-01f},{9.7364426e-01f,-2.2807208e-01f},
{9.7293997e-01f,-2.310581e-01f},{9.722265e-01f,-2.3404196e-01f},{9.715039e-01f,-2.370236e-01f},{9.7077215e-01f,-2.4000302e-01f},
{9.7003126e-01f,-2.4298018e-01f},{9.6928126e-01f,-2.4595505e-01f},{9.685221e-01f,-2.4892761e-01f},{9.677538e-01f,-2.518978e-01f},
{9.6697646e-01f,-2.5486565e-01f},{9.6619e-01f,-2.578311e-01f},{9.6539444e-01f,-2.607941e-01f},{9.645898e-01f,-2.6375467e-01f},
{9.6377605e-01f,-2.6671275e-01f},{9.6295327e-01f,-2.696683e-01f},{9.621214e-01f,-2.7262136e-01f},{9.6128047e-01f,-2.7557182e-01f},
{9.604305e-01f,-2.785197e-01f},{9.5957154e-01f,-2.8146493e-01f},{9.5870346e-01f,-2.8440753e-01f},{9.5782644e-01f,-2.8734747e-01f},
{9.5694035e-01f,-2.9028466e-01f},{9.5604527e-01f,-2.9321915e-01f},{9.551412e-01f,-2.961509e-01f},{9.542281e-01f,-2.9907984e-01f},
{9.53306e-01f,-3.0200595e-01f},{9.52375e-01f,-3.0492923e-01f},{9.51435e-01f,-3.0784965e-01f},{9.5048606e-01f,-3.1076714e-01f},
{9.4952816e-01f,-3.1368175e-01f},{9.485614e-01f,-3.1659338e-01f},{9.475856e-01f,-3.1950203e-01f},{9.466009e-01f,-3.224077e-01f},
{9.456073e-01f,-3.253103e-01f},{9.446048e-01f,-3.2820985e-01f},{9.4359344e-01f,-3.311063e-01f},{9.425732e-01f,-3.3399966e-01f},
{9.4154406e-01f,-3.3688986e-01f},{9.4050604e-01f,-3.3977687e-01f},{9.394592e-01f,-3.4266073e-01f},{9.3840355e-01f,-3.4554133e-01f},
{9.37339e-01f,-3.4841868e-01f},{9.3626565e-01f,-3.5129276e-01f},{9.351835e-01f,-3.5416353e-01f},{9.340925e-01f,-3.5703096e-01f},
{9.329928e-01f,-3.5989505e-01f},{9.318843e-01f,-3.6275572e-01f},{9.3076694e-01f,-3.6561298e-01f},{9.296409e-01f,-3.6846682e-01f},
{9.285061e-01f,-3.713172e-01f},{9.273625e-01f,-3.7416407e-01f},{9.262102e-01f,-3.7700742e-01f},{9.2504925e-01f,-3.798472e-01f},
{1.0e+00f,0.0e+00f},{9.9998116e-01f,-6.1358847e-03f},{9.999247e-01f,-1.2271538e-02f},{9.998306e-01f,-1.840673e-02f},
{9.996988e-01f,-2.4541229e-02f},{9.995294e-01f,-3.0674804e-02f},{9.9932235e-01f,-3.6807224e-02f},{9.9907774e-01f,-4.293826e-02f},
{9.9879545e-01f,-4.9067676e-02f},{9.9847555e-01f,-5.5195246e-02f},{9.981181e-01f,-6.1320737e-02f},{9.9772304e-01f,-6.744392e-02f},
{9.9729043e-01f,-7.356457e-02f},{9.968203e-01f,-7.968244e-02f},{9.963126e-01f,-8.579731e-02f},{9.957674e-01f,-9.1908954e-02f},
{9.951847e-01f,-9.801714e-02f},{9.945646e-01f,-1.0412163e-01f},{9.93907e-01f,-1.10222206e-01f},{9.932119e-01f,-1.1631863e-01f},
{9.9247956e-01f,-1.2241068e-01f},{9.9170977e-01f,-1.284981e-01f},{9.9090266e-01f,-1.345807e-01f},{9.900582e-01f,-1.4065824e-01f},
{9.891765e-01f,-1.4673047e-01f},{9.882576e-01f,-1.5279719e-01f},{9.873014e-01f,-1.5885815e-01f},{9.863081e-01f,-1.6491312e-01f},
{9.8527765e-01f,-1.7096189e-01f},{9.842101e-01f,-1.7700422e-01f},{9.831055e-01f,-1.8303989e-01f},{9.819639e-01f,-1.8906866e-01f},
{9.8078525e-01f,-1.9509032e-01f},{9.795698e-01f,-2.0110464e-01f},{9.783174e-01f,-2.0711137e-01f},{9.7702813e-01f,-2.1311031e-01f},
{9.757021e-01f,-2.1910124e-01f},{9.7433937e-01f,-2.2508392e-01f},{9.7293997e-01f,-2.310581e-01f},{9.715039e-01f,-2.370236e-01f},
{9.7003126e-01f,-2.4298018e-01f},{9.685221e-01f,-2.4892761e-01f},{9.6697646e-01f,-2.5486565e-01f},{9.6539444e-01f,-2.607941e-01f},
{9.6377605e-01f,-2.6671275e-01f},{9.621214e-01f,-2.7262136e-01f},{9.604305e-01f,-2.785197e-01f},{9.5870346e-01f,-2.8440753e-01f},
{9.5694035e-01f,-2.9028466e-01f},{9.551412e-01f,-2.961509e-01f},{9.53306e-01f,-3.0200595e-01f},{9.51435e-01f,-3.0784965e-01f},
{9.4952816e-01f,-3.1368175e-01f},{9.475856e-01f,-3.1950203e-01f},{9.456073e-01f,-3.253103e-01f},{9.4359344e-01f,-3.311063e-01f},
{9.4154406e-01f,-3.3688986e-01f},{9.394592e-01f,-3.4266073e-01f},{9.37339e-01f,-3.4841868e-01f},{9.351835e-01f,-3.5416353e-01f},
{9.329928e-01f,-3.5989505e-01f},{9.3076694e-01f,-3.6561298e-01f},{9.285061e-01f,-3.713172e-01f},{9.262102e-01f,-3.7700742e-01f},
{9.238795e-01f,-3.8268343e-01f},{9.2151403e-01f,-3.8834503e-01f},{9.191139e-01f,-3.9399204e-01f},{9.166791e-01f,-3.996242e-01f},
{9.142098e-01f,-4.052413e-01f},{9.1170603e-01f,-4.1084316e-01f},{9.09168e-01f,-4.1642955e-01f},{9.065957e-01f,-4.2200026e-01f},
{9.039893e-01f,-4.2755508e-01f},{9.013488e-01f,-4.3309382e-01f},{8.986745e-01f,-4.3861625e-01f},{8.9596623e-01f,-4.4412214e-01f},
{8.932243e-01f,-4.4961134e-01f},{8.9044875e-01f,-4.5508358e-01f},{8.8763964e-01f,-4.6053872e-01f},{8.847971e-01f,-4.659765e-01f},
{8.819213e-01f,-4.7139674e-01f},{8.790122e-01f,-4.7679922e-01f},{8.760701e-01f,-4.8218378e-01f},{8.73095e-01f,-4.8755017e-01f},
{8.7008697e-01f,-4.928982e-01f},{8.6704624e-01f,-4.9822766e-01f},{8.6397284e-01f,-5.0353837e-01f},{8.6086696e-01f,-5.0883013e-01f},
{8.577286e-01f,-5.1410276e-01f},{8.54558e-01f,-5.19356e-01f},{8.513552e-01f,-5.2458966e-01f},{8.4812033e-01f,-5.2980363e-01f},
{8.448536e-01f,-5.3499764e-01f},{8.41555e-01f,-5.4017144e-01f},{8.382247e-01f,-5.45325e-01f},{8.348629e-01f,-5.5045795e-01f},
{8.314696e-01f,-5.5557024e-01f},{8.2804507e-01f,-5.6066155e-01f},{8.245893e-01f,-5.657318e-01f},{8.211025e-01f,-5.7078075e-01f},
{8.175848e-01f,-5.7580817e-01f},{8.140363e-01f,-5.8081394e-01f},{8.1045717e-01f,-5.8579785e-01f},{8.068476e-01f,-5.907597e-01f},
{8.032075e-01f,-5.956993e-01f},{7.9953724e-01f,-6.0061646e-01f},{7.958369e-01f,-6.0551107e-01f},{7.9210657e-01f,-6.103828e-01f},
{7.883464e-01f,-6.152316e-01f},{7.8455657e-01f,-6.200572e-01f},{7.807372e-01f,-6.248595e-01f},{7.768885e-01f,-6.2963825e-01f},
{7.7301043e-01f,-6.343933e-01f},{7.6910335e-01f,-6.3912445e-01f},{7.6516724e-01f,-6.4383155e-01f},{7.612024e-01f,-6.485144e-01f},
{7.572088e-01f,-6.5317285e-01f},{7.531868e-01f,-6.578067e-01f},{7.491364e-01f,-6.624158e-01f},{7.4505776e-01f,-6.6699994e-01f},
{7.409511e-01f,-6.71559e-01f},{7.368166e-01f,-6.760927e-01f},{7.326543e-01f,-6.80601e-01f},{7.2846437e-01f,-6.850837e-01f},
{7.242471e-01f,-6.8954057e-01f},{7.2000253e-01f,-6.9397146e-01f},{7.1573085e-01f,-6.9837624e-01f},{7.114322e-01f,-7.0275474e-01f},
{1.0e+00f,0.0e+00f},{9.999576e-01f,-9.203754e-03f},{9.998306e-01f,-1.840673e-02f},{9.996188e-01f,-2.7608145e-02f},
{9.9932235e-01f,-3.6807224e-02f},{9.989413e-01f,-4.600318e-02f},{9.9847555e-01f,-5.5195246e-02f},{9.979253e-01f,-6.438263e-02f},
{9.9729043e-01f,-7.356457e-02f},{9.965711e-01f,-8.274026e-02f},{9.957674e-01f,-9.1908954e-02f},{9.948793e-01f,-1.0106986e-01f},
{9.93907e-01f,-1.10222206e-01f},{9.928504e-01f,-1.19365215e-01f},{9.9170977e-01f,-1.284981e-01f},{9.904851e-01f,-1.3762012e-01f},
{9.891765e-01f,-1.4673047e-01f},{9.8778415e-01f,-1.558284e-01f},{9.863081e-01f,-1.6491312e-01f},{9.847485e-01f,-1.7398387e-01f},
{9.831055e-01f,-1.8303989e-01f},{9.813792e-01f,-1.920804e-01f},{9.795698e-01f,-2.0110464e-01f},{9.7767735e-01f,-2.1011184e-01f},
{9.757021e-01f,-2.1910124e-01f},{9.7364426e-01f,-2.2807208e-01f},{9.715039e-01f,-2.370236e-01f},{9.6928126e-01f,-2.4595505e-01f},
{9.6697646e-01f,-2.5486565e-01f},{9.645898e-01f,-2.6375467e-01f},{9.621214e-01f,-2.7262136e-01f},{9.5957154e-01f,-2.8146493e-01f},
{9.5694035e-01f,-2.9028466e-01f},{9.542281e-01f,-2.9907984e-01f},{9.51435e-01f,-3.0784965e-01f},{9.485614e-01f,-3.1659338e-01f},
{9.456073e-01f,-3.253103e-01f},{9.425732e-01f,-3.3399966e-01f},{9.394592e-01f,-3.4266073e-01f},{9.3626565e-01f,-3.5129276e-01f},
{9.329928e-01f,-3.5989505e-01f},{9.296409e-01f,-3.6846682e-01f},{9.262102e-01f,-3.7700742e-01f},{9.227011e-01f,-3.8551605e-01f},
{9.191139e-01f,-3.9399204e-01f},{9.154487e-01f,-4.0243465e-01f},{9.1170603e-01f,-4.1084316e-01f},{9.078861e-01f,-4.192169e-01f},
{9.039893e-01f,-4.2755508e-01f},{9.000159e-01f,-4.358571e-01f},{8.9596623e-01f,-4.4412214e-01f},{8.918407e-01f,-4.5234957e-01f},
{8.8763964e-01f,-4.6053872e-01f},{8.8336337e-01f,-4.6868882e-01f},{8.790122e-01f,-4.7679922e-01f},{8.7458664e-01f,-4.8486924e-01f},
{8.7008697e-01f,-4.928982e-01f},{8.655136e-01f,-5.0088537e-01f},{8.6086696e-01f,-5.0883013e-01f},{8.5614735e-01f,-5.167318e-01f},
{8.513552e-01f,-5.2458966e-01f},{8.464909e-01f,-5.324031e-01f},{8.41555e-01f,-5.4017144e-01f},{8.3654773e-01f,-5.4789406e-01f},
{8.314696e-01f,-5.5557024e-01f},{8.2632107e-01f,-5.6319934e-01f},{8.211025e-01f,-5.7078075e-01f},{8.1581444e-01f,-5.7831377e-01f},
{8.1045717e-01f,-5.8579785e-01f},{8.0503136e-01f,-5.932323e-01f},{7.9953724e-01f,-6.0061646e-01f},{7.939755e-01f,-6.079498e-01f},
{7.883464e-01f,-6.152316e-01f},{7.826506e-01f,-6.2246126e-01f},{7.768885e-01f,-6.2963825e-01f},{7.710605e-01f,-6.3676184e-01f},
{7.6516724e-01f,-6.4383155e-01f},{7.592092e-01f,-6.5084666e-01f},{7.531868e-01f,-6.578067e-01f},{7.471006e-01f,-6.64711e-01f},
{7.409511e-01f,-6.71559e-01f},{7.347389e-01f,-6.7835003e-01f},{7.2846437e-01f,-6.850837e-01f},{7.221282e-01f,-6.917592e-01f},
{7.1573085e-01f,-6.9837624e-01f},{7.092728e-01f,-7.0493406e-01f},{7.0275474e-01f,-7.114322e-01f},{6.961771e-01f,-7.1787006e-01f},
{6.8954057e-01f,-7.242471e-01f},{6.8284553e-01f,-7.3056275e-01f},{6.760927e-01f,-7.368166e-01f},{6.692826e-01f,-7.4300796e-01f},
{6.624158e-01f,-7.491364e-01f},{6.5549284e-01f,-7.552014e-01f},{6.485144e-01f,-7.612024e-01f},{6.4148104e-01f,-7.671389e-01f},
{6.343933e-01f,-7.7301043e-01f},{6.272518e-01f,-7.788165e-01f},{6.200572e-01f,-7.8455657e-01f},{6.128101e-01f,-7.902302e-01f},
{6.0551107e-01f,-7.958369e-01f},{5.981607e-01f,-8.0137616e-01f},{5.907597e-01f,-8.068476e-01f},{5.8330864e-01f,-8.122506e-01f},
{5.7580817e-01f,-8.175848e-01f},{5.6825894e-01f,-8.228498e-01f},{5.6066155e-01f,-8.2804507e-01f},{5.530167e-01f,-8.331702e-01f},
{5.45325e-01f,-8.382247e-01f},{5.3758705e-01f,-8.4320825e-01f},{5.2980363e-01f,-8.4812033e-01f},{5.219753e-01f,-8.529606e-01f},
{5.1410276e-01f,-8.577286e-01f},{5.0618666e-01f,-8.6242396e-01f},{4.9822766e-01f,-8.6704624e-01f},{4.9022648e-01f,-8.715951e-01f},
{4.8218378e-01f,-8.760701e-01f},{4.741002e-01f,-8.804709e-01f},{4.659765e-01f,-8.847971e-01f},{4.578133e-01f,-8.8904834e-01f},
{4.4961134e-01f,-8.932243e-01f},{4.4137126e-01f,-8.9732456e-01f},{4.3309382e-01f,-9.013488e-01f},{4.2477968e-01f,-9.0529674e-01f},
{4.1642955e-01f,-9.09168e-01f},{4.0804416e-01f,-9.129622e-01f},{3.996242e-01f,-9.166791e-01f},{3.9117038e-01f,-9.203183e-01f},
{1.0e+00f,0.0e+00f},{9.999247e-01f,-1.2271538e-02f},{9.996988e-01f,-2.4541229e-02f},{9.9932235e-01f,-3.6807224e-02f},
{9.9879545e-01f,-4.9067676e-02f},{9.981181e-01f,-6.1320737e-02f},{9.9729043e-01f,-7.356457e-02f},{9.963126e-01f,-8.579731e-02f},
{9.951847e-01f,-9.801714e-02f},{9.93907e-01f,-1.10222206e-01f},{9.9247956e-01f,-1.2241068e-01f},{9.9090266e-01f,-1.345807e-01f},
{9.891765e-01f,-1.4673047e-01f},{9.873014e-01f,-1.5885815e-01f},{9.8527765e-01f,-1.7096189e-01f},{9.831055e-01f,-1.8303989e-01f},
{9.8078525e-01f,-1.9509032e-01f},{9.783174e-01f,-2.0711137e-01f},{9.757021e-01f,-2.1910124e-01f},{9.7293997e-01f,-2.310581e-01f},
{9.7003126e-01f,-2.4298018e-01f},{9.6697646e-01f,-2.5486565e-01f},{9.6377605e-01f,-2.6671275e-01f},{9.604305e-01f,-2.785197e-01f},
{9.5694035e-01f,-2.9028466e-01f},{9.53306e-01f,-3.0200595e-01f},{9.4952816e-01f,-3.1368175e-01f},{9.456073e-01f,-3.253103e-01f},
{9.4154406e-01f,-3.3688986e-01f},{9.37339e-01f,-3.4841868e-01f},{9.329928e-01f,-3.5989505e-01f},{9.285061e-01f,-3.713172e-01f},
{9.238795e-01f,-3.8268343e-01f},{9.191139e-01f,-3.9399204e-01f},{9.142098e-01f,-4.052413e-01f},{9.09168e-01f,-4.1642955e-01f},
{9.039893e-01f,-4.2755508e-01f},{8.986745e-01f,-4.3861625e-01f},{8.932243e-01f,-4.4961134e-01f},{8.8763964e-01f,-4.6053872e-01f},
{8.819213e-01f,-4.7139674e-01f},{8.760701e-01f,-4.8218378e-01f},{8.7008697e-01f,-4.928982e-01f},{8.6397284e-01f,-5.0353837e-01f},
{8.577286e-01f,-5.1410276e-01f},{8.513552e-01f,-5.2458966e-01f},{8.448536e-01f,-5.3499764e-01f},{8.382247e-01f,-5.45325e-01f},
{8.314696e-01f,-5.5557024e-01f},{8.245893e-01f,-5.657318e-01f},{8.175848e-01f,-5.7580817e-01f},{8.1045717e-01f,-5.8579785e-01f},
{8.032075e-01f,-5.956993e-01f},{7.958369e-01f,-6.0551107e-01f},{7.883464e-01f,-6.152316e-01f},{7.807372e-01f,-6.248595e-01f},
{7.7301043e-01f,-6.343933e-01f},{7.6516724e-01f,-6.4383155e-01f},{7.572088e-01f,-6.5317285e-01f},{7.491364e-01f,-6.624158e-01f},
{7.409511e-01f,-6.71559e-01f},{7.326543e-01f,-6.80601e-01f},{7.242471e-01f,-6.8954057e-01f},{7.1573085e-01f,-6.9837624e-01f},
{7.0710677e-01f,-7.0710677e-01f},{6.9837624e-01f,-7.1573085e-01f},{6.8954057e-01f,-7.242471e-01f},{6.80601e-01f,-7.326543e-01f},
{6.71559e-01f,-7.409511e-01f},{6.624158e-01f,-7.491364e-01f},{6.5317285e-01f,-7.572088e-01f},{6.4383155e-01f,-7.6516724e-01f},
{6.343933e-01f,-7.7301043e-01f},{6.248595e-01f,-7.807372e-01f},{6.152316e-01f,-7.883464e-01f},{6.0551107e-01f,-7.958369e-01f},
{5.956993e-01f,-8.032075e-01f},{5.8579785e-01f,-8.1045717e-01f},{5.7580817e-01f,-8.175848e-01f},{5.657318e-01f,-8.245893e-01f},
{5.5557024e-01f,-8.314696e-01f},{5.45325e-01f,-8.382247e-01f},{5.3499764e-01f,-8.448536e-01f},{5.2458966e-01f,-8.513552e-01f},
{5.1410276e-01f,-8.577286e-01f},{5.0353837e-01f,-8.6397284e-01f},{4.928982e-01f,-8.7008697e-01f},{4.8218378e-01f,-8.760701e-01f},
{4.7139674e-01f,-8.819213e-01f},{4.6053872e-01f,-8.8763964e-01f},{4.4961134e-01f,-8.932243e-01f},{4.3861625e-01f,-8.986745e-01f},
{4.2755508e-01f,-9.039893e-01f},{4.1642955e-01f,-9.09168e-01f},{4.052413e-01f,-9.142098e-01f},{3.9399204e-01f,-9.191139e-01f},
{3.8268343e-01f,-9.238795e-01f},{3.713172e-01f,-9.285061e-01f},{3.5989505e-01f,-9.329928e-01f},{3.4841868e-01f,-9.37339e-01f},
{3.3688986e-01f,-9.4154406e-01f},{3.253103e-01f,-9.456073e-01f},{3.1368175e-01f,-9.4952816e-01f},{3.0200595e-01f,-9.53306e-01f},
{2.9028466e-01f,-9.5694035e-01f},{2.785197e-01f,-9.604305e-01f},{2.6671275e-01f,-9.6377605e-01f},{2.5486565e-01f,-9.6697646e-01f},
{2.4298018e-01f,-9.7003126e-01f},{2.310581e-01f,-9.7293997e-01f},{2.1910124e-01f,-9.757021e-01f},{2.0711137e-01f,-9.783174e-01f},
{1.9509032e-01f,-9.8078525e-01f},{1.8303989e-01f,-9.831055e-01f},{1.7096189e-01f,-9.8527765e-01f},{1.5885815e-01f,-9.873014e-01f},
{1.4673047e-01f,-9.891765e-01f},{1.345807e-01f,-9.9090266e-01f},{1.2241068e-01f,-9.9247956e-01f},{1.10222206e-01f,-9.93907e-01f},
{9.801714e-02f,-9.951847e-01f},{8.579731e-02f,-9.963126e-01f},{7.356457e-02f,-9.9729043e-01f},{6.1320737e-02f,-9.981181e-01f},
{4.9067676e-02f,-9.9879545e-01f},{3.6807224e-02f,-9.9932235e-01f},{2.4541229e-02f,-9.996988e-01f},{1.2271538e-02f,-9.999247e-01f},
{1.0e+00f,0.0e+00f},{9.9988234e-01f,-1.5339206e-02f},{9.995294e-01f,-3.0674804e-02f},{9.989413e-01f,-4.600318e-02f},
{9.981181e-01f,-6.1320737e-02f},{9.9706006e-01f,-7.6623864e-02f},{9.957674e-01f,-9.1908954e-02f},{9.9424046e-01f,-1.0717242e-01f},
{9.9247956e-01f,-1.2241068e-01f},{9.904851e-01f,-1.3762012e-01f},{9.882576e-01f,-1.5279719e-01f},{9.857975e-01f,-1.6793829e-01f},
{9.831055e-01f,-1.8303989e-01f},{9.801821e-01f,-1.980984e-01f},{9.7702813e-01f,-2.1311031e-01f},{9.7364426e-01f,-2.2807208e-01f},
{9.7003126e-01f,-2.4298018e-01f},{9.6619e-01f,-2.578311e-01f},{9.621214e-01f,-2.7262136e-01f},{9.5782644e-01f,-2.8734747e-01f},
{9.53306e-01f,-3.0200595e-01f},{9.485614e-01f,-3.1659338e-01f},{9.4359344e-01f,-3.311063e-01f},{9.3840355e-01f,-3.4554133e-01f},
{9.329928e-01f,-3.5989505e-01f},{9.273625e-01f,-3.7416407e-01f},{9.2151403e-01f,-3.8834503e-01f},{9.154487e-01f,-4.0243465e-01f},
{9.09168e-01f,-4.1642955e-01f},{9.026733e-01f,-4.303265e-01f},{8.9596623e-01f,-4.4412214e-01f},{8.8904834e-01f,-4.578133e-01f},
{8.819213e-01f,-4.7139674e-01f},{8.7458664e-01f,-4.8486924e-01f},{8.6704624e-01f,-4.9822766e-01f},{8.593018e-01f,-5.114688e-01f},
{8.513552e-01f,-5.2458966e-01f},{8.4320825e-01f,-5.3758705e-01f},{8.348629e-01f,-5.5045795e-01f},{8.2632107e-01f,-5.6319934e-01f},
{8.175848e-01f,-5.7580817e-01f},{8.0865616e-01f,-5.882816e-01f},{7.9953724e-01f,-6.0061646e-01f},{7.902302e-01f,-6.128101e-01f},
{7.807372e-01f,-6.248595e-01f},{7.710605e-01f,-6.3676184e-01f},{7.612024e-01f,-6.485144e-01f},{7.5116515e-01f,-6.6011435e-01f},
{7.409511e-01f,-6.71559e-01f},{7.3056275e-01f,-6.8284553e-01f},{7.2000253e-01f,-6.9397146e-01f},{7.092728e-01f,-7.0493406e-01f},
{6.9837624e-01f,-7.1573085e-01f},{6.8731534e-01f,-7.263591e-01f},{6.760927e-01f,-7.368166e-01f},{6.64711e-01f,-7.471006e-01f},
{6.5317285e-01f,-7.572088e-01f},{6.4148104e-01f,-7.671389e-01f},{6.2963825e-01f,-7.768885e-01f},{6.176473e-01f,-7.864552e-01f},
{6.0551107e-01f,-7.958369e-01f},{5.932323e-01f,-8.0503136e-01f},{5.8081394e-01f,-8.140363e-01f},{5.6825894e-01f,-8.228498e-01f},
{5.5557024e-01f,-8.314696e-01f},{5.427508e-01f,-8.398938e-01f},{5.2980363e-01f,-8.4812033e-01f},{5.167318e-01f,-8.5614735e-01f},
{5.0353837e-01f,-8.6397284e-01f},{4.9022648e-01f,-8.715951e-01f},{4.7679922e-01f,-8.790122e-01f},{4.632598e-01f,-8.8622254e-01f},
{4.4961134e-01f,-8.932243e-01f},{4.358571e-01f,-9.000159e-01f},{4.2200026e-01f,-9.065957e-01f},{4.0804416e-01f,-9.129622e-01f},
{3.9399204e-01f,-9.191139e-01f},{3.798472e-01f,-9.2504925e-01f},{3.6561298e-01f,-9.3076694e-01f},{3.5129276e-01f,-9.3626565e-01f},
{3.3688986e-01f,-9.4154406e-01f},{3.224077e-01f,-9.466009e-01f},{3.0784965e-01f,-9.51435e-01f},{2.9321915e-01f,-9.5604527e-01f},
{2.785197e-01f,-9.604305e-01f},{2.6375467e-01f,-9.645898e-01f},{2.4892761e-01f,-9.685221e-01f},{2.3404196e-01f,-9.722265e-01f},
{2.1910124e-01f,-9.757021e-01f},{2.0410897e-01f,-9.789482e-01f},{1.8906866e-01f,-9.819639e-01f},{1.7398387e-01f,-9.847485e-01f},
{1.5885815e-01f,-9.873014e-01f},{1.4369503e-01f,-9.89622e-01f},{1.284981e-01f,-9.9170977e-01f},{1.1327095e-01f,-9.935641e-01f},
{9.801714e-02f,-9.951847e-01f},{8.274026e-02f,-9.965711e-01f},{6.744392e-02f,-9.9772304e-01f},{5.2131705e-02f,-9.9864024e-01f},
{3.6807224e-02f,-9.9932235e-01f},{2.147408e-02f,-9.997694e-01f},{6.1358847e-03f,-9.9998116e-01f},{-9.203754e-03f,-9.999576e-01f},
{-2.4541229e-02f,-9.996988e-01f},{-3.9872926e-02f,-9.9920475e-01f},{-5.5195246e-02f,-9.9847555e-01f},{-7.0504576e-02f,-9.9751145e-01f},
{-8.579731e-02f,-9.963126e-01f},{-1.0106986e-01f,-9.948793e-01f},{-1.1631863e-01f,-9.932119e-01f},{-1.3154003e-01f,-9.9131083e-01f},
{-1.4673047e-01f,-9.891765e-01f},{-1.618864e-01f,-9.868094e-01f},{-1.7700422e-01f,-9.842101e-01f},{-1.920804e-01f,-9.813792e-01f},
{-2.0711137e-01f,-9.783174e-01f},{-2.2209363e-01f,-9.7502536e-01f},{-2.370236e-01f,-9.715039e-01f},{-2.518978e-01f,-9.677538e-01f},
{-2.6671275e-01f,-9.6377605e-01f},{-2.8146493e-01f,-9.5957154e-01f},{-2.961509e-01f,-9.551412e-01f},{-3.1076714e-01f,-9.5048606e-01f},
{-3.253103e-01f,-9.456073e-01f},{-3.3977687e-01f,-9.4050604e-01f},{-3.5416353e-01f,-9.351835e-01f},{-3.6846682e-01f,-9.296409e-01f},
{1.0e+00f,0.0e+00f},{9.998306e-01f,-1.840673e-02f},{9.9932235e-01f,-3.6807224e-02f},{9.9847555e-01f,-5.5195246e-02f},
{9.9729043e-01f,-7.356457e-02f},{9.957674e-01f,-9.1908954e-02f},{9.93907e-01f,-1.10222206e-01f},{9.9170977e-01f,-1.284981e-01f},
{9.891765e-01f,-1.4673047e-01f},{9.863081e-01f,-1.6491312e-01f},{9.831055e-01f,-1.8303989e-01f},{9.795698e-01f,-2.0110464e-01f},
{9.757021e-01f,-2.1910124e-01f},{9.715039e-01f,-2.370236e-01f},{9.6697646e-01f,-2.5486565e-01f},{9.621214e-01f,-2.7262136e-01f},
{9.5694035e-01f,-2.9028466e-01f},{9.51435e-01f,-3.0784965e-01f},{9.456073e-01f,-3.253103e-01f},{9.394592e-01f,-3.4266073e-01f},
{9.329928e-01f,-3.5989505e-01f},{9.262102e-01f,-3.7700742e-01f},{9.191139e-01f,-3.9399204e-01f},{9.1170603e-01f,-4.1084316e-01f},
{9.039893e-01f,-4.2755508e-01f},{8.9596623e-01f,-4.4412214e-01f},{8.8763964e-01f,-4.6053872e-01f},{8.790122e-01f,-4.7679922e-01f},
{8.7008697e-01f,-4.928982e-01f},{8.6086696e-01f,-5.0883013e-01f},{8.513552e-01f,-5.2458966e-01f},{8.41555e-01f,-5.4017144e-01f},
{8.314696e-01f,-5.5557024e-01f},{8.211025e-01f,-5.7078075e-01f},{8.1045717e-01f,-5.8579785e-01f},{7.9953724e-01f,-6.0061646e-01f},
{7.883464e-01f,-6.152316e-01f},{7.768885e-01f,-6.2963825e-01f},{7.6516724e-01f,-6.4383155e-01f},{7.531868e-01f,-6.578067e-01f},
{7.409511e-01f,-6.71559e-01f},{7.2846437e-01f,-6.850837e-01f},{7.1573085e-01f,-6.9837624e-01f},{7.0275474e-01f,-7.114322e-01f},
{6.8954057e-01f,-7.242471e-01f},{6.760927e-01f,-7.368166e-01f},{6.624158e-01f,-7.491364e-01f},{6.485144e-01f,-7.612024e-01f},
{6.343933e-01f,-7.7301043e-01f},{6.200572e-01f,-7.8455657e-01f},{6.0551107e-01f,-7.958369e-01f},{5.907597e-01f,-8.068476e-01f},
{5.7580817e-01f,-8.175848e-01f},{5.6066155e-01f,-8.2804507e-01f},{5.45325e-01f,-8.382247e-01f},{5.2980363e-01f,-8.4812033e-01f},
{5.1410276e-01f,-8.577286e-01f},{4.9822766e-01f,-8.6704624e-01f},{4.8218378e-01f,-8.760701e-01f},{4.659765e-01f,-8.847971e-01f},
{4.4961134e-01f,-8.932243e-01f},{4.3309382e-01f,-9.013488e-01f},{4.1642955e-01f,-9.09168e-01f},{3.996242e-01f,-9.166791e-01f},
{3.8268343e-01f,-9.238795e-01f},{3.6561298e-01f,-9.3076694e-01f},{3.4841868e-01f,-9.37339e-01f},{3.311063e-01f,-9.4359344e-01f},
{3.1368175e-01f,-9.4952816e-01f},{2.961509e-01f,-9.551412e-01f},{2.785197e-01f,-9.604305e-01f},{2.607941e-01f,-9.6539444e-01f},
{2.4298018e-01f,-9.7003126e-01f},{2.2508392e-01f,-9.7433937e-01f},{2.0711137e-01f,-9.783174e-01f},{1.8906866e-01f,-9.819639e-01f},
{1.7096189e-01f,-9.8527765e-01f},{1.5279719e-01f,-9.882576e-01f},{1.345807e-01f,-9.9090266e-01f},{1.1631863e-01f,-9.932119e-01f},
{9.801714e-02f,-9.951847e-01f},{7.968244e-02f,-9.968203e-01f},{6.1320737e-02f,-9.981181e-01f},{4.293826e-02f,-9.9907774e-01f},
{2.4541229e-02f,-9.996988e-01f},{6.1358847e-03f,-9.9998116e-01f},{-1.2271538e-02f,-9.999247e-01f},{-3.0674804e-02f,-9.995294e-01f},
{-4.9067676e-02f,-9.9879545e-01f},{-6.744392e-02f,-9.9772304e-01f},{-8.579731e-02f,-9.963126e-01f},{-1.0412163e-01f,-9.945646e-01f},
{-1.2241068e-01f,-9.9247956e-01f},{-1.4065824e-01f,-9.900582e-01f},{-1.5885815e-01f,-9.873014e-01f},{-1.7700422e-01f,-9.842101e-01f},
{-1.9509032e-01f,-9.8078525e-01f},{-2.1311031e-01f,-9.7702813e-01f},{-2.310581e-01f,-9.7293997e-01f},{-2.4892761e-01f,-9.685221e-01f},
{-2.6671275e-01f,-9.6377605e-01f},{-2.8440753e-01f,-9.5870346e-01f},{-3.0200595e-01f,-9.53306e-01f},{-3.1950203e-01f,-9.475856e-01f},
{-3.3688986e-01f,-9.4154406e-01f},{-3.5416353e-01f,-9.351835e-01f},{-3.713172e-01f,-9.285061e-01f},{-3.8834503e-01f,-9.2151403e-01f},
{-4.052413e-01f,-9.142098e-01f},{-4.2200026e-01f,-9.065957e-01f},{-4.3861625e-01f,-8.986745e-01f},{-4.5508358e-01f,-8.9044875e-01f},
{-4.7139674e-01f,-8.819213e-01f},{-4.8755017e-01f,-8.73095e-01f},{-5.0353837e-01f,-8.6397284e-01f},{-5.19356e-01f,-8.54558e-01f},
{-5.3499764e-01f,-8.448536e-01f},{-5.5045795e-01f,-8.348629e-01f},{-5.657318e-01f,-8.245893e-01f},{-5.8081394e-01f,-8.140363e-01f},
{-5.956993e-01f,-8.032075e-01f},{-6.103828e-01f,-7.9210657e-01f},{-6.248595e-01f,-7.807372e-01f},{-6.3912445e-01f,-7.6910335e-01f},
{-6.5317285e-01f,-7.572088e-01f},{-6.6699994e-01f,-7.4505776e-01f},{-6.80601e-01f,-7.326543e-01f},{-6.9397146e-01f,-7.2000253e-01f},
{1.0e+00f,0.0e+00f},{9.997694e-01f,-2.147408e-02f},{9.9907774e-01f,-4.293826e-02f},{9.979253e-01f,-6.438263e-02f},
{9.963126e-01f,-8.579731e-02f},{9.9424046e-01f,-1.0717242e-01f},{9.9170977e-01f,-1.284981e-01f},{9.8872167e-01f,-1.4976454e-01f},
{9.8527765e-01f,-1.7096189e-01f},{9.813792e-01f,-1.920804e-01f},{9.7702813e-01f,-2.1311031e-01f},{9.722265e-01f,-2.3404196e-01f},
{9.6697646e-01f,-2.5486565e-01f},{9.6128047e-01f,-2.7557182e-01f},{9.551412e-01f,-2.961509e-01f},{9.485614e-01f,-3.1659338e-01f},
{9.4154406e-01f,-3.3688986e-01f},{9.340925e-01f,-3.5703096e-01f},{9.262102e-01f,-3.7700742e-01f},{9.179008e-01f,-3.9681e-01f},
{9.09168e-01f,-4.1642955e-01f},{9.000159e-01f,-4.358571e-01f},{8.9044875e-01f,-4.5508358e-01f},{8.804709e-01f,-4.741002e-01f},
{8.7008697e-01f,-4.928982e-01f},{8.593018e-01f,-5.114688e-01f},{8.4812033e-01f,-5.2980363e-01f},{8.3654773e-01f,-5.4789406e-01f},
{8.245893e-01f,-5.657318e-01f},{8.122506e-01f,-5.8330864e-01f},{7.9953724e-01f,-6.0061646e-01f},{7.864552e-01f,-6.176473e-01f},
{7.7301043e-01f,-6.343933e-01f},{7.592092e-01f,-6.5084666e-01f},{7.4505776e-01f,-6.6699994e-01f},{7.3056275e-01f,-6.8284553e-01f},
{7.1573085e-01f,-6.9837624e-01f},{7.005688e-01f,-7.1358484e-01f},{6.850837e-01f,-7.2846437e-01f},{6.692826e-01f,-7.4300796e-01f},
{6.5317285e-01f,-7.572088e-01f},{6.3676184e-01f,-7.710605e-01f},{6.200572e-01f,-7.8455657e-01f},{6.030666e-01f,-7.9769087e-01f},
{5.8579785e-01f,-8.1045717e-01f},{5.6825894e-01f,-8.228498e-01f},{5.5045795e-01f,-8.348629e-01f},{5.324031e-01f,-8.464909e-01f},
{5.1410276e-01f,-8.577286e-01f},{4.9556527e-01f,-8.685707e-01f},{4.7679922e-01f,-8.790122e-01f},{4.578133e-01f,-8.8904834e-01f},
{4.3861625e-01f,-8.986745e-01f},{4.192169e-01f,-9.078861e-01f},{3.996242e-01f,-9.166791e-01f},{3.798472e-01f,-9.2504925e-01f},
{3.5989505e-01f,-9.329928e-01f},{3.3977687e-01f,-9.4050604e-01f},{3.1950203e-01f,-9.475856e-01f},{2.9907984e-01f,-9.542281e-01f},
{2.785197e-01f,-9.604305e-01f},{2.578311e-01f,-9.6619e-01f},{2.370236e-01f,-9.715039e-01f},{2.161068e-01f,-9.7636974e-01f},
{1.9509032e-01f,-9.8078525e-01f},{1.7398387e-01f,-9.847485e-01f},{1.5279719e-01f,-9.882576e-01f},{1.3154003e-01f,-9.9131083e-01f},
{1.10222206e-01f,-9.93907e-01f},{8.885355e-02f,-9.960447e-01f},{6.744392e-02f,-9.9772304e-01f},{4.600318e-02f,-9.989413e-01f},
{2.4541229e-02f,-9.996988e-01f},{3.0679568e-03f,-9.999953e-01f},{-1.840673e-02f,-9.998306e-01f},{-3.9872926e-02f,-9.9920475e-01f},
{-6.1320737e-02f,-9.981181e-01f},{-8.274026e-02f,-9.965711e-01f},{-1.0412163e-01f,-9.945646e-01f},{-1.2545498e-01f,-9.920993e-01f},
{-1.4673047e-01f,-9.891765e-01f},{-1.6793829e-01f,-9.857975e-01f},{-1.8906866e-01f,-9.819639e-01f},{-2.1011184e-01f,-9.7767735e-01f},
{-2.310581e-01f,-9.7293997e-01f},{-2.518978e-01f,-9.677538e-01f},{-2.7262136e-01f,-9.621214e-01f},{-2.9321915e-01f,-9.5604527e-01f},
{-3.1368175e-01f,-9.4952816e-01f},{-3.3399966e-01f,-9.425732e-01f},{-3.5416353e-01f,-9.351835e-01f},{-3.7416407e-01f,-9.273625e-01f},
{-3.9399204e-01f,-9.191139e-01f},{-4.1363832e-01f,-9.104413e-01f},{-4.3309382e-01f,-9.013488e-01f},{-4.5234957e-01f,-8.918407e-01f},
{-4.7139674e-01f,-8.819213e-01f},{-4.9022648e-01f,-8.715951e-01f},{-5.0883013e-01f,-8.6086696e-01f},{-5.2719915e-01f,-8.4974176e-01f},
{-5.45325e-01f,-8.382247e-01f},{-5.6319934e-01f,-8.2632107e-01f},{-5.8081394e-01f,-8.140363e-01f},{-5.981607e-01f,-8.0137616e-01f},
{-6.152316e-01f,-7.883464e-01f},{-6.3201874e-01f,-7.749531e-01f},{-6.485144e-01f,-7.612024e-01f},{-6.64711e-01f,-7.471006e-01f},
{-6.80601e-01f,-7.326543e-01f},{-6.961771e-01f,-7.1787006e-01f},{-7.114322e-01f,-7.0275474e-01f},{-7.263591e-01f,-6.8731534e-01f},
{-7.409511e-01f,-6.71559e-01f},{-7.552014e-01f,-6.5549284e-01f},{-7.6910335e-01f,-6.3912445e-01f},{-7.826506e-01f,-6.2246126e-01f},
{-7.958369e-01f,-6.0551107e-01f},{-8.0865616e-01f,-5.882816e-01f},{-8.211025e-01f,-5.7078075e-01f},{-8.331702e-01f,-5.530167e-01f},
{-8.448536e-01f,-5.3499764e-01f},{-8.5614735e-01f,-5.167318e-01f},{-8.6704624e-01f,-4.9822766e-01f},{-8.775453e-01f,-4.7949377e-01f},
{-8.8763964e-01f,-4.6053872e-01f},{-8.9732456e-01f,-4.4137126e-01f},{-9.065957e-01f,-4.2200026e-01f},{-9.154487e-01f,-4.0243465e-01f},
{1.0e+00f,0.0e+00f},{9.996988e-01f,-2.4541229e-02f},{9.9879545e-01f,-4.9067676e-02f},{9.9729043e-01f,-7.356457e-02f},
{9.951847e-01f,-9.801714e-02f},{9.9247956e-01f,-1.2241068e-01f},{9.891765e-01f,-1.4673047e-01f},{9.8527765e-01f,-1.7096189e-01f},
{9.8078525e-01f,-1.9509032e-01f},{9.757021e-01f,-2.1910124e-01f},{9.7003126e-01f,-2.4298018e-01f},{9.6377605e-01f,-2.6671275e-01f},
{9.5694035e-01f,-2.9028466e-01f},{9.4952816e-01f,-3.1368175e-01f},{9.4154406e-01f,-3.3688986e-01f},{9.329928e-01f,-3.5989505e-01f},
{9.238795e-01f,-3.8268343e-01f},{9.142098e-01f,-4.052413e-01f},{9.039893e-01f,-4.2755508e-01f},{8.932243e-01f,-4.4961134e-01f},
{8.819213e-01f,-4.7139674e-01f},{8.7008697e-01f,-4.928982e-01f},{8.577286e-01f,-5.1410276e-01f},{8.448536e-01f,-5.3499764e-01f},
{8.314696e-01f,-5.5557024e-01f},{8.175848e-01f,-5.7580817e-01f},{8.032075e-01f,-5.956993e-01f},{7.883464e-01f,-6.152316e-01f},
{7.7301043e-01f,-6.343933e-01f},{7.572088e-01f,-6.5317285e-01f},{7.409511e-01f,-6.71559e-01f},{7.242471e-01f,-6.8954057e-01f},
{7.0710677e-01f,-7.0710677e-01f},{6.8954057e-01f,-7.242471e-01f},{6.71559e-01f,-7.409511e-01f},{6.5317285e-01f,-7.572088e-01f},
{6.343933e-01f,-7.7301043e-01f},{6.152316e-01f,-7.883464e-01f},{5.956993e-01f,-8.032075e-01f},{5.7580817e-01f,-8.175848e-01f},
{5.5557024e-01f,-8.314696e-01f},{5.3499764e-01f,-8.448536e-01f},{5.1410276e-01f,-8.577286e-01f},{4.928982e-01f,-8.7008697e-01f},
{4.7139674e-01f,-8.819213e-01f},{4.4961134e-01f,-8.932243e-01f},{4.2755508e-01f,-9.039893e-01f},{4.052413e-01f,-9.142098e-01f},
{3.8268343e-01f,-9.238795e-01f},{3.5989505e-01f,-9.329928e-01f},{3.3688986e-01f,-9.4154406e-01f},{3.1368175e-01f,-9.4952816e-01f},
{2.9028466e-01f,-9.5694035e-01f},{2.6671275e-01f,-9.6377605e-01f},{2.4298018e-01f,-9.7003126e-01f},{2.1910124e-01f,-9.757021e-01f},
{1.9509032e-01f,-9.8078525e-01f},{1.7096189e-01f,-9.8527765e-01f},{1.4673047e-01f,-9.891765e-01f},{1.2241068e-01f,-9.9247956e-01f},
{9.801714e-02f,-9.951847e-01f},{7.356457e-02f,-9.9729043e-01f},{4.9067676e-02f,-9.9879545e-01f},{2.4541229e-02f,-9.996988e-01f},
{6.123234e-17f,-1.0e+00f},{-2.4541229e-02f,-9.996988e-01f},{-4.9067676e-02f,-9.9879545e-01f},{-7.356457e-02f,-9.9729043e-01f},
{-9.801714e-02f,-9.951847e-01f},{-1.2241068e-01f,-9.9247956e-01f},{-1.4673047e-01f,-9.891765e-01f},{-1.7096189e-01f,-9.8527765e-01f},
{-1.9509032e-01f,-9.8078525e-01f},{-2.1910124e-01f,-9.757021e-01f},{-2.4298018e-01f,-9.7003126e-01f},{-2.6671275e-01f,-9.6377605e-01f},
{-2.9028466e-01f,-9.5694035e-01f},{-3.1368175e-01f,-9.4952816e-01f},{-3.3688986e-01f,-9.4154406e-01f},{-3.5989505e-01f,-9.329928e-01f},
{-3.8268343e-01f,-9.238795e-01f},{-4.052413e-01f,-9.142098e-01f},{-4.2755508e-01f,-9.039893e-01f},{-4.4961134e-01f,-8.932243e-01f},
{-4.7139674e-01f,-8.819213e-01f},{-4.928982e-01f,-8.7008697e-01f},{-5.1410276e-01f,-8.577286e-01f},{-5.3499764e-01f,-8.448536e-01f},
{-5.5557024e-01f,-8.314696e-01f},{-5.7580817e-01f,-8.175848e-01f},{-5.956993e-01f,-8.032075e-01f},{-6.152316e-01f,-7.883464e-01f},
{-6.343933e-01f,-7.7301043e-01f},{-6.5317285e-01f,-7.572088e-01f},{-6.71559e-01f,-7.409511e-01f},{-6.8954057e-01f,-7.242471e-01f},
{-7.0710677e-01f,-7.0710677e-01f},{-7.242471e-01f,-6.8954057e-01f},{-7.409511e-01f,-6.71559e-01f},{-7.572088e-01f,-6.5317285e-01f},
{-7.7301043e-01f,-6.343933e-01f},{-7.883464e-01f,-6.152316e-01f},{-8.032075e-01f,-5.956993e-01f},{-8.175848e-01f,-5.7580817e-01f},
{-8.314696e-01f,-5.5557024e-01f},{-8.448536e-01f,-5.3499764e-01f},{-8.577286e-01f,-5.1410276e-01f},{-8.7008697e-01f,-4.928982e-01f},
{-8.819213e-01f,-4.7139674e-01f},{-8.932243e-01f,-4.4961134e-01f},{-9.039893e-01f,-4.2755508e-01f},{-9.142098e-01f,-4.052413e-01f},
{-9.238795e-01f,-3.8268343e-01f},{-9.329928e-01f,-3.5989505e-01f},{-9.4154406e-01f,-3.3688986e-01f},{-9.4952816e-01f,-3.1368175e-01f},
{-9.5694035e-01f,-2.9028466e-01f},{-9.6377605e-01f,-2.6671275e-01f},{-9.7003126e-01f,-2.4298018e-01f},{-9.757021e-01f,-2.1910124e-01f},
{-9.8078525e-01f,-1.9509032e-01f},{-9.8527765e-01f,-1.7096189e-01f},{-9.891765e-01f,-1.4673047e-01f},{-9.9247956e-01f,-1.2241068e-01f},
{-9.951847e-01f,-9.801714e-02f},{-9.9729043e-01f,-7.356457e-02f},{-9.9879545e-01f,-4.9067676e-02f},{-9.996988e-01f,-2.4541229e-02f},
{1.0e+00f,0.0e+00f},{9.996188e-01f,-2.7608145e-02f},{9.9847555e-01f,-5.5195246e-02f},{9.965711e-01f,-8.274026e-02f},
{9.93907e-01f,-1.10222206e-01f},{9.904851e-01f,-1.3762012e-01f},{9.863081e-01f,-1.6491312e-01f},{9.813792e-01f,-1.920804e-01f},
{9.757021e-01f,-2.1910124e-01f},{9.6928126e-01f,-2.4595505e-01f},{9.621214e-01f,-2.7262136e-01f},{9.542281e-01f,-2.9907984e-01f},
{9.456073e-01f,-3.253103e-01f},{9.3626565e-01f,-3.5129276e-01f},{9.262102e-01f,-3.7700742e-01f},{9.154487e-01f,-4.0243465e-01f},
{9.039893e-01f,-4.2755508e-01f},{8.918407e-01f,-4.5234957e-01f},{8.790122e-01f,-4.7679922e-01f},{8.655136e-01f,-5.0088537e-01f},
{8.513552e-01f,-5.2458966e-01f},{8.3654773e-01f,-5.4789406e-01f},{8.211025e-01f,-5.7078075e-01f},{8.0503136e-01f,-5.932323e-01f},
{7.883464e-01f,-6.152316e-01f},{7.710605e-01f,-6.3676184e-01f},{7.531868e-01f,-6.578067e-01f},{7.347389e-01f,-6.7835003e-01f},
{7.1573085e-01f,-6.9837624e-01f},{6.961771e-01f,-7.1787006e-01f},{6.760927e-01f,-7.368166e-01f},{6.5549284e-01f,-7.552014e-01f},
{6.343933e-01f,-7.7301043e-01f},{6.128101e-01f,-7.902302e-01f},{5.907597e-01f,-8.068476e-01f},{5.6825894e-01f,-8.228498e-01f},
{5.45325e-01f,-8.382247e-01f},{5.219753e-01f,-8.529606e-01f},{4.9822766e-01f,-8.6704624e-01f},{4.741002e-01f,-8.804709e-01f},
{4.4961134e-01f,-8.932243e-01f},{4.2477968e-01f,-9.0529674e-01f},{3.996242e-01f,-9.166791e-01f},{3.7416407e-01f,-9.273625e-01f},
{3.4841868e-01f,-9.37339e-01f},{3.224077e-01f,-9.466009e-01f},{2.961509e-01f,-9.551412e-01f},{2.696683e-01f,-9.6295327e-01f},
{2.4298018e-01f,-9.7003126e-01f},{2.161068e-01f,-9.7636974e-01f},{1.8906866e-01f,-9.819639e-01f},{1.618864e-01f,-9.868094e-01f},
{1.345807e-01f,-9.9090266e-01f},{1.0717242e-01f,-9.9424046e-01f},{7.968244e-02f,-9.968203e-01f},{5.2131705e-02f,-9.9864024e-01f},
{2.4541229e-02f,-9.996988e-01f},{-3.0679568e-03f,-9.999953e-01f},{-3.0674804e-02f,-9.995294e-01f},{-5.8258265e-02f,-9.9830157e-01f},
{-8.579731e-02f,-9.963126e-01f},{-1.1327095e-01f,-9.935641e-01f},{-1.4065824e-01f,-9.900582e-01f},{-1.6793829e-01f,-9.857975e-01f},
{-1.9509032e-01f,-9.8078525e-01f},{-2.2209363e-01f,-9.7502536e-01f},{-2.4892761e-01f,-9.685221e-01f},{-2.7557182e-01f,-9.6128047e-01f},
{-3.0200595e-01f,-9.53306e-01f},{-3.2820985e-01f,-9.446048e-01f},{-3.5416353e-01f,-9.351835e-01f},{-3.798472e-01f,-9.2504925e-01f},
{-4.052413e-01f,-9.142098e-01f},{-4.303265e-01f,-9.026733e-01f},{-4.5508358e-01f,-8.9044875e-01f},{-4.7949377e-01f,-8.775453e-01f},
{-5.0353837e-01f,-8.6397284e-01f},{-5.2719915e-01f,-8.4974176e-01f},{-5.5045795e-01f,-8.348629e-01f},{-5.7329714e-01f,-8.193475e-01f},
{-5.956993e-01f,-8.032075e-01f},{-6.176473e-01f,-7.864552e-01f},{-6.3912445e-01f,-7.6910335e-01f},{-6.6011435e-01f,-7.5116515e-01f},
{-6.80601e-01f,-7.326543e-01f},{-7.005688e-01f,-7.1358484e-01f},{-7.2000253e-01f,-6.9397146e-01f},{-7.388873e-01f,-6.73829e-01f},
{-7.572088e-01f,-6.5317285e-01f},{-7.749531e-01f,-6.3201874e-01f},{-7.9210657e-01f,-6.103828e-01f},{-8.0865616e-01f,-5.882816e-01f},
{-8.245893e-01f,-5.657318e-01f},{-8.398938e-01f,-5.427508e-01f},{-8.54558e-01f,-5.19356e-01f},{-8.685707e-01f,-4.9556527e-01f},
{-8.819213e-01f,-4.7139674e-01f},{-8.945995e-01f,-4.4686884e-01f},{-9.065957e-01f,-4.2200026e-01f},{-9.179008e-01f,-3.9681e-01f},
{-9.285061e-01f,-3.713172e-01f},{-9.3840355e-01f,-3.4554133e-01f},{-9.475856e-01f,-3.1950203e-01f},{-9.5604527e-01f,-2.9321915e-01f},
{-9.6377605e-01f,-2.6671275e-01f},{-9.7077215e-01f,-2.4000302e-01f},{-9.7702813e-01f,-2.1311031e-01f},{-9.825393e-01f,-1.8605515e-01f},
{-9.873014e-01f,-1.5885815e-01f},{-9.9131083e-01f,-1.3154003e-01f},{-9.945646e-01f,-1.0412163e-01f},{-9.9706006e-01f,-7.6623864e-02f},
{-9.9879545e-01f,-4.9067676e-02f},{-9.997694e-01f,-2.147408e-02f},{-9.9998116e-01f,6.1358847e-03f},{-9.994306e-01f,3.3741172e-02f},
{-9.981181e-01f,6.1320737e-02f},{-9.960447e-01f,8.885355e-02f},{-9.932119e-01f,1.1631863e-01f},{-9.89622e-01f,1.4369503e-01f},
{-9.8527765e-01f,1.7096189e-01f},{-9.801821e-01f,1.980984e-01f},{-9.7433937e-01f,2.2508392e-01f},{-9.677538e-01f,2.518978e-01f},
{-9.604305e-01f,2.785197e-01f},{-9.52375e-01f,3.0492923e-01f},{-9.4359344e-01f,3.311063e-01f},{-9.340925e-01f,3.5703096e-01f},
{1.0e+00f,0.0e+00f},{9.995294e-01f,-3.0674804e-02f},{9.981181e-01f,-6.1320737e-02f},{9.957674e-01f,-9.1908954e-02f},
{9.9247956e-01f,-1.2241068e-01f},{9.882576e-01f,-1.5279719e-01f},{9.831055e-01f,-1.8303989e-01f},{9.7702813e-01f,-2.1311031e-01f},
{9.7003126e-01f,-2.4298018e-01f},{9.621214e-01f,-2.7262136e-01f},{9.53306e-01f,-3.0200595e-01f},{9.4359344e-01f,-3.311063e-01f},
{9.329928e-01f,-3.5989505e-01f},{9.2151403e-01f,-3.8834503e-01f},{9.09168e-01f,-4.1642955e-01f},{8.9596623e-01f,-4.4412214e-01f},
{8.819213e-01f,-4.7139674e-01f},{8.6704624e-01f,-4.9822766e-01f},{8.513552e-01f,-5.2458966e-01f},{8.348629e-01f,-5.5045795e-01f},
{8.175848e-01f,-5.7580817e-01f},{7.9953724e-01f,-6.0061646e-01f},{7.807372e-01f,-6.248595e-01f},{7.612024e-01f,-6.485144e-01f},
{7.409511e-01f,-6.71559e-01f},{7.2000253e-01f,-6.9397146e-01f},{6.9837624e-01f,-7.1573085e-01f},{6.760927e-01f,-7.368166e-01f},
{6.5317285e-01f,-7.572088e-01f},{6.2963825e-01f,-7.768885e-01f},{6.0551107e-01f,-7.958369e-01f},{5.8081394e-01f,-8.140363e-01f},
{5.5557024e-01f,-8.314696e-01f},{5.2980363e-01f,-8.4812033e-01f},{5.0353837e-01f,-8.6397284e-01f},{4.7679922e-01f,-8.790122e-01f},
{4.4961134e-01f,-8.932243e-01f},{4.2200026e-01f,-9.065957e-01f},{3.9399204e-01f,-9.191139e-01f},{3.6561298e-01f,-9.3076694e-01f},
{3.3688986e-01f,-9.4154406e-01f},{3.0784965e-01f,-9.51435e-01f},{2.785197e-01f,-9.604305e-01f},{2.4892761e-01f,-9.685221e-01f},
{2.1910124e-01f,-9.757021e-01f},{1.8906866e-01f,-9.819639e-01f},{1.5885815e-01f,-9.873014e-01f},{1.284981e-01f,-9.9170977e-01f},
{9.801714e-02f,-9.951847e-01f},{6.744392e-02f,-9.9772304e-01f},{3.6807224e-02f,-9.9932235e-01f},{6.1358847e-03f,-9.9998116e-01f},
{-2.4541229e-02f,-9.996988e-01f},{-5.5195246e-02f,-9.9847555e-01f},{-8.579731e-02f,-9.963126e-01f},{-1.1631863e-01f,-9.932119e-01f},
{-1.4673047e-01f,-9.891765e-01f},{-1.7700422e-01f,-9.842101e-01f},{-2.0711137e-01f,-9.783174e-01f},{-2.370236e-01f,-9.715039e-01f},
{-2.6671275e-01f,-9.6377605e-01f},{-2.961509e-01f,-9.551412e-01f},{-3.253103e-01f,-9.456073e-01f},{-3.5416353e-01f,-9.351835e-01f},
{-3.8268343e-01f,-9.238795e-01f},{-4.1084316e-01f,-9.1170603e-01f},{-4.3861625e-01f,-8.986745e-01f},{-4.659765e-01f,-8.847971e-01f},
{-4.928982e-01f,-8.7008697e-01f},{-5.19356e-01f,-8.54558e-01f},{-5.45325e-01f,-8.382247e-01f},{-5.7078075e-01f,-8.211025e-01f},
{-5.956993e-01f,-8.032075e-01f},{-6.200572e-01f,-7.8455657e-01f},{-6.4383155e-01f,-7.6516724e-01f},{-6.6699994e-01f,-7.4505776e-01f},
{-6.8954057e-01f,-7.242471e-01f},{-7.114322e-01f,-7.0275474e-01f},{-7.326543e-01f,-6.80601e-01f},{-7.531868e-01f,-6.578067e-01f},
{-7.7301043e-01f,-6.343933e-01f},{-7.9210657e-01f,-6.103828e-01f},{-8.1045717e-01f,-5.8579785e-01f},{-8.2804507e-01f,-5.6066155e-01f},
{-8.448536e-01f,-5.3499764e-01f},{-8.6086696e-01f,-5.0883013e-01f},{-8.760701e-01f,-4.8218378e-01f},{-8.9044875e-01f,-4.5508358e-01f},
{-9.039893e-01f,-4.2755508e-01f},{-9.166791e-01f,-3.996242e-01f},{-9.285061e-01f,-3.713172e-01f},{-9.394592e-01f,-3.4266073e-01f},
{-9.4952816e-01f,-3.1368175e-01f},{-9.5870346e-01f,-2.8440753e-01f},{-9.6697646e-01f,-2.5486565e-01f},{-9.7433937e-01f,-2.2508392e-01f},
{-9.8078525e-01f,-1.9509032e-01f},{-9.863081e-01f,-1.6491312e-01f},{-9.9090266e-01f,-1.345807e-01f},{-9.945646e-01f,-1.0412163e-01f},
{-9.9729043e-01f,-7.356457e-02f},{-9.9907774e-01f,-4.293826e-02f},{-9.999247e-01f,-1.2271538e-02f},{-9.998306e-01f,1.840673e-02f},
{-9.9879545e-01f,4.9067676e-02f},{-9.968203e-01f,7.968244e-02f},{-9.93907e-01f,1.10222206e-01f},{-9.900582e-01f,1.4065824e-01f},
{-9.8527765e-01f,1.7096189e-01f},{-9.795698e-01f,2.0110464e-01f},{-9.7293997e-01f,2.310581e-01f},{-9.6539444e-01f,2.607941e-01f},
{-9.5694035e-01f,2.9028466e-01f},{-9.475856e-01f,3.1950203e-01f},{-9.37339e-01f,3.4841868e-01f},{-9.262102e-01f,3.7700742e-01f},
{-9.142098e-01f,4.052413e-01f},{-9.013488e-01f,4.3309382e-01f},{-8.8763964e-01f,4.6053872e-01f},{-8.73095e-01f,4.8755017e-01f},
{-8.577286e-01f,5.1410276e-01f},{-8.41555e-01f,5.4017144e-01f},{-8.245893e-01f,5.657318e-01f},{-8.068476e-01f,5.907597e-01f},
{-7.883464e-01f,6.152316e-01f},{-7.6910335e-01f,6.3912445e-01f},{-7.491364e-01f,6.624158e-01f},{-7.2846437e-01f,6.850837e-01f},
{1.0e+00f,0.0e+00f},{9.994306e-01f,-3.3741172e-02f},{9.9772304e-01f,-6.744392e-02f},{9.948793e-01f,-1.0106986e-01f},
{9.9090266e-01f,-1.345807e-01f},{9.857975e-01f,-1.6793829e-01f},{9.795698e-01f,-2.0110464e-01f},{9.722265e-01f,-2.3404196e-01f},
{9.6377605e-01f,-2.6671275e-01f},{9.542281e-01f,-2.9907984e-01f},{9.4359344e-01f,-3.311063e-01f},{9.318843e-01f,-3.6275572e-01f},
{9.191139e-01f,-3.9399204e-01f},{9.0529674e-01f,-4.2477968e-01f},{8.9044875e-01f,-4.5508358e-01f},{8.7458664e-01f,-4.8486924e-01f},
{8.577286e-01f,-5.1410276e-01f},{8.398938e-01f,-5.427508e-01f},{8.211025e-01f,-5.7078075e-01f},{8.0137616e-01f,-5.981607e-01f},
{7.807372e-01f,-6.248595e-01f},{7.592092e-01f,-6.5084666e-01f},{7.368166e-01f,-6.760927e-01f},{7.1358484e-01f,-7.005688e-01f},
{6.8954057e-01f,-7.242471e-01f},{6.64711e-01f,-7.471006e-01f},{6.3912445e-01f,-7.6910335e-01f},{6.128101e-01f,-7.902302e-01f},
{5.8579785e-01f,-8.1045717e-01f},{5.581185e-01f,-8.297612e-01f},{5.2980363e-01f,-8.4812033e-01f},{5.0088537e-01f,-8.655136e-01f},
{4.7139674e-01f,-8.819213e-01f},{4.4137126e-01f,-8.9732456e-01f},{4.1084316e-01f,-9.1170603e-01f},{3.798472e-01f,-9.2504925e-01f},
{3.4841868e-01f,-9.37339e-01f},{3.1659338e-01f,-9.485614e-01f},{2.8440753e-01f,-9.5870346e-01f},{2.518978e-01f,-9.677538e-01f},
{2.1910124e-01f,-9.757021e-01f},{1.8605515e-01f,-9.825393e-01f},{1.5279719e-01f,-9.882576e-01f},{1.19365215e-01f,-9.928504e-01f},
{8.579731e-02f,-9.963126e-01f},{5.2131705e-02f,-9.9864024e-01f},{1.840673e-02f,-9.998306e-01f},{-1.5339206e-02f,-9.9988234e-01f},
{-4.9067676e-02f,-9.9879545e-01f},{-8.274026e-02f,-9.965711e-01f},{-1.1631863e-01f,-9.932119e-01f},{-1.4976454e-01f,-9.8872167e-01f},
{-1.8303989e-01f,-9.831055e-01f},{-2.161068e-01f,-9.7636974e-01f},{-2.4892761e-01f,-9.685221e-01f},{-2.8146493e-01f,-9.5957154e-01f},
{-3.1368175e-01f,-9.4952816e-01f},{-3.4554133e-01f,-9.3840355e-01f},{-3.7700742e-01f,-9.262102e-01f},{-4.0804416e-01f,-9.129622e-01f},
{-4.3861625e-01f,-8.986745e-01f},{-4.6868882e-01f,-8.8336337e-01f},{-4.9822766e-01f,-8.6704624e-01f},{-5.2719915e-01f,-8.4974176e-01f},
{-5.5557024e-01f,-8.314696e-01f},{-5.8330864e-01f,-8.122506e-01f},{-6.103828e-01f,-7.9210657e-01f},{-6.3676184e-01f,-7.710605e-01f},
{-6.624158e-01f,-7.491364e-01f},{-6.8731534e-01f,-7.263591e-01f},{-7.114322e-01f,-7.0275474e-01f},{-7.347389e-01f,-6.7835003e-01f},
{-7.572088e-01f,-6.5317285e-01f},{-7.788165e-01f,-6.272518e-01f},{-7.9953724e-01f,-6.0061646e-01f},{-8.193475e-01f,-5.7329714e-01f},
{-8.382247e-01f,-5.45325e-01f},{-8.5614735e-01f,-5.167318e-01f},{-8.73095e-01f,-4.8755017e-01f},{-8.8904834e-01f,-4.578133e-01f},
{-9.039893e-01f,-4.2755508e-01f},{-9.179008e-01f,-3.9681e-01f},{-9.3076694e-01f,-3.6561298e-01f},{-9.425732e-01f,-3.3399966e-01f},
{-9.53306e-01f,-3.0200595e-01f},{-9.6295327e-01f,-2.696683e-01f},{-9.715039e-01f,-2.370236e-01f},{-9.789482e-01f,-2.0410897e-01f},
{-9.8527765e-01f,-1.7096189e-01f},{-9.904851e-01f,-1.3762012e-01f},{-9.945646e-01f,-1.0412163e-01f},{-9.9751145e-01f,-7.0504576e-02f},
{-9.9932235e-01f,-3.6807224e-02f},{-9.999953e-01f,-3.0679568e-03f},{-9.995294e-01f,3.0674804e-02f},{-9.979253e-01f,6.438263e-02f},
{-9.951847e-01f,9.801714e-02f},{-9.9131083e-01f,1.3154003e-01f},{-9.863081e-01f,1.6491312e-01f},{-9.801821e-01f,1.980984e-01f},
{-9.7293997e-01f,2.310581e-01f},{-9.645898e-01f,2.6375467e-01f},{-9.551412e-01f,2.961509e-01f},{-9.446048e-01f,3.2820985e-01f},
{-9.329928e-01f,3.5989505e-01f},{-9.203183e-01f,3.9117038e-01f},{-9.065957e-01f,4.2200026e-01f},{-8.918407e-01f,4.5234957e-01f},
{-8.760701e-01f,4.8218378e-01f},{-8.593018e-01f,5.114688e-01f},{-8.41555e-01f,5.4017144e-01f},{-8.228498e-01f,5.6825894e-01f},
{-8.032075e-01f,5.956993e-01f},{-7.826506e-01f,6.2246126e-01f},{-7.612024e-01f,6.485144e-01f},{-7.388873e-01f,6.73829e-01f},
{-7.1573085e-01f,6.9837624e-01f},{-6.917592e-01f,7.221282e-01f},{-6.6699994e-01f,7.4505776e-01f},{-6.4148104e-01f,7.671389e-01f},
{-6.152316e-01f,7.883464e-01f},{-5.882816e-01f,8.0865616e-01f},{-5.6066155e-01f,8.2804507e-01f},{-5.324031e-01f,8.464909e-01f},
{-5.0353837e-01f,8.6397284e-01f},{-4.741002e-01f,8.804709e-01f},{-4.4412214e-01f,8.9596623e-01f},{-4.1363832e-01f,9.104413e-01f},
{1.0e+00f,0.0e+00f},{9.9932235e-01f,-3.6807224e-02f},{9.9729043e-01f,-7.356457e-02f},{9.93907e-01f,-1.10222206e-01f},
{9.891765e-01f,-1.4673047e-01f},{9.831055e-01f,-1.8303989e-01f},{9.757021e-01f,-2.1910124e-01f},{9.6697646e-01f,-2.5486565e-01f},
{9.5694035e-01f,-2.9028466e-01f},{9.456073e-01f,-3.253103e-01f},{9.329928e-01f,-3.5989505e-01f},{9.191139e-01f,-3.9399204e-01f},
{9.039893e-01f,-4.2755508e-01f},{8.8763964e-01f,-4.6053872e-01f},{8.7008697e-01f,-4.928982e-01f},{8.513552e-01f,-5.2458966e-01f},
{8.314696e-01f,-5.5557024e-01f},{8.1045717e-01f,-5.8579785e-01f},{7.883464e-01f,-6.152316e-01f},{7.6516724e-01f,-6.4383155e-01f},
{7.409511e-01f,-6.71559e-01f},{7.1573085e-01f,-6.9837624e-01f},{6.8954057e-01f,-7.242471e-01f},{6.624158e-01f,-7.491364e-01f},
{6.343933e-01f,-7.7301043e-01f},{6.0551107e-01f,-7.958369e-01f},{5.7580817e-01f,-8.175848e-01f},{5.45325e-01f,-8.382247e-01f},
{5.1410276e-01f,-8.577286e-01f},{4.8218378e-01f,-8.760701e-01f},{4.4961134e-01f,-8.932243e-01f},{4.1642955e-01f,-9.09168e-01f},
{3.8268343e-01f,-9.238795e-01f},{3.4841868e-01f,-9.37339e-01f},{3.1368175e-01f,-9.4952816e-01f},{2.785197e-01f,-9.604305e-01f},
{2.4298018e-01f,-9.7003126e-01f},{2.0711137e-01f,-9.783174e-01f},{1.7096189e-01f,-9.8527765e-01f},{1.345807e-01f,-9.9090266e-01f},
{9.801714e-02f,-9.951847e-01f},{6.1320737e-02f,-9.981181e-01f},{2.4541229e-02f,-9.996988e-01f},{-1.2271538e-02f,-9.999247e-01f},
{-4.9067676e-02f,-9.9879545e-01f},{-8.579731e-02f,-9.963126e-01f},{-1.2241068e-01f,-9.9247956e-01f},{-1.5885815e-01f,-9.873014e-01f},
{-1.9509032e-01f,-9.8078525e-01f},{-2.310581e-01f,-9.7293997e-01f},{-2.6671275e-01f,-9.6377605e-01f},{-3.0200595e-01f,-9.53306e-01f},
{-3.3688986e-01f,-9.4154406e-01f},{-3.713172e-01f,-9.285061e-01f},{-4.052413e-01f,-9.142098e-01f},{-4.3861625e-01f,-8.986745e-01f},
{-4.7139674e-01f,-8.819213e-01f},{-5.0353837e-01f,-8.6397284e-01f},{-5.3499764e-01f,-8.448536e-01f},{-5.657318e-01f,-8.245893e-01f},
{-5.956993e-01f,-8.032075e-01f},{-6.248595e-01f,-7.807372e-01f},{-6.5317285e-01f,-7.572088e-01f},{-6.80601e-01f,-7.326543e-01f},
{-7.0710677e-01f,-7.0710677e-01f},{-7.326543e-01f,-6.80601e-01f},{-7.572088e-01f,-6.5317285e-01f},{-7.807372e-01f,-6.248595e-01f},
{-8.032075e-01f,-5.956993e-01f},{-8.245893e-01f,-5.657318e-01f},{-8.448536e-01f,-5.3499764e-01f},{-8.6397284e-01f,-5.0353837e-01f},
{-8.819213e-01f,-4.7139674e-01f},{-8.986745e-01f,-4.3861625e-01f},{-9.142098e-01f,-4.052413e-01f},{-9.285061e-01f,-3.713172e-01f},
{-9.4154406e-01f,-3.3688986e-01f},{-9.53306e-01f,-3.0200595e-01f},{-9.6377605e-01f,-2.6671275e-01f},{-9.7293997e-01f,-2.310581e-01f},
{-9.8078525e-01f,-1.9509032e-01f},{-9.873014e-01f,-1.5885815e-01f},{-9.9247956e-01f,-1.2241068e-01f},{-9.963126e-01f,-8.579731e-02f},
{-9.9879545e-01f,-4.9067676e-02f},{-9.999247e-01f,-1.2271538e-02f},{-9.996988e-01f,2.4541229e-02f},{-9.981181e-01f,6.1320737e-02f},
{-9.951847e-01f,9.801714e-02f},{-9.9090266e-01f,1.345807e-01f},{-9.8527765e-01f,1.7096189e-01f},{-9.783174e-01f,2.0711137e-01f},
{-9.7003126e-01f,2.4298018e-01f},{-9.604305e-01f,2.785197e-01f},{-9.4952816e-01f,3.1368175e-01f},{-9.37339e-01f,3.4841868e-01f},
{-9.238795e-01f,3.8268343e-01f},{-9.09168e-01f,4.1642955e-01f},{-8.932243e-01f,4.4961134e-01f},{-8.760701e-01f,4.8218378e-01f},
{-8.577286e-01f,5.1410276e-01f},{-8.382247e-01f,5.45325e-01f},{-8.175848e-01f,5.7580817e-01f},{-7.958369e-01f,6.0551107e-01f},
{-7.7301043e-01f,6.343933e-01f},{-7.491364e-01f,6.624158e-01f},{-7.242471e-01f,6.8954057e-01f},{-6.9837624e-01f,7.1573085e-01f},
{-6.71559e-01f,7.409511e-01f},{-6.4383155e-01f,7.6516724e-01f},{-6.152316e-01f,7.883464e-01f},{-5.8579785e-01f,8.1045717e-01f},
{-5.5557024e-01f,8.314696e-01f},{-5.2458966e-01f,8.513552e-01f},{-4.928982e-01f,8.7008697e-01f},{-4.6053872e-01f,8.8763964e-01f},
{-4.2755508e-01f,9.039893e-01f},{-3.9399204e-01f,9.191139e-01f},{-3.5989505e-01f,9.329928e-01f},{-3.253103e-01f,9.456073e-01f},
{-2.9028466e-01f,9.5694035e-01f},{-2.5486565e-01f,9.6697646e-01f},{-2.1910124e-01f,9.757021e-01f},{-1.8303989e-01f,9.831055e-01f},
{-1.4673047e-01f,9.891765e-01f},{-1.10222206e-01f,9.93907e-01f},{-7.356457e-02f,9.9729043e-01f},{-3.6807224e-02f,9.9932235e-01f},
{1.0e+00f,0.0e+00f},{9.9920475e-01f,-3.9872926e-02f},{9.968203e-01f,-7.968244e-02f},{9.928504e-01f,-1.19365215e-01f},
{9.873014e-01f,-1.5885815e-01f},{9.801821e-01f,-1.980984e-01f},{9.715039e-01f,-2.370236e-01f},{9.6128047e-01f,-2.7557182e-01f},
{9.4952816e-01f,-3.1368175e-01f},{9.3626565e-01f,-3.5129276e-01f},{9.2151403e-01f,-3.8834503e-01f},{9.0529674e-01f,-4.2477968e-01f},
{8.8763964e-01f,-4.6053872e-01f},{8.685707e-01f,-4.9556527e-01f},{8.4812033e-01f,-5.2980363e-01f},{8.2632107e-01f,-5.6319934e-01f},
{8.032075e-01f,-5.956993e-01f},{7.788165e-01f,-6.272518e-01f},{7.531868e-01f,-6.578067e-01f},{7.263591e-01f,-6.8731534e-01f},
{6.9837624e-01f,-7.1573085e-01f},{6.692826e-01f,-7.4300796e-01f},{6.3912445e-01f,-7.6910335e-01f},{6.079498e-01f,-7.939755e-01f},
{5.7580817e-01f,-8.175848e-01f},{5.427508e-01f,-8.398938e-01f},{5.0883013e-01f,-8.6086696e-01f},{4.741002e-01f,-8.804709e-01f},
{4.3861625e-01f,-8.986745e-01f},{4.0243465e-01f,-9.154487e-01f},{3.6561298e-01f,-9.3076694e-01f},{3.2820985e-01f,-9.446048e-01f},
{2.9028466e-01f,-9.5694035e-01f},{2.518978e-01f,-9.677538e-01f},{2.1311031e-01f,-9.7702813e-01f},{1.7398387e-01f,-9.847485e-01f},
{1.345807e-01f,-9.9090266e-01f},{9.49635e-02f,-9.954808e-01f},{5.5195246e-02f,-9.9847555e-01f},{1.5339206e-02f,-9.9988234e-01f},
{-2.4541229e-02f,-9.996988e-01f},{-6.438263e-02f,-9.979253e-01f},{-1.0412163e-01f,-9.945646e-01f},{-1.4369503e-01f,-9.89622e-01f},
{-1.8303989e-01f,-9.831055e-01f},{-2.2209363e-01f,-9.7502536e-01f},{-2.607941e-01f,-9.6539444e-01f},{-2.9907984e-01f,-9.542281e-01f},
{-3.3688986e-01f,-9.4154406e-01f},{-3.7416407e-01f,-9.273625e-01f},{-4.1084316e-01f,-9.1170603e-01f},{-4.4686884e-01f,-8.945995e-01f},
{-4.8218378e-01f,-8.760701e-01f},{-5.167318e-01f,-8.5614735e-01f},{-5.5045795e-01f,-8.348629e-01f},{-5.8330864e-01f,-8.122506e-01f},
{-6.152316e-01f,-7.883464e-01f},{-6.4617604e-01f,-7.631884e-01f},{-6.760927e-01f,-7.368166e-01f},{-7.0493406e-01f,-7.092728e-01f},
{-7.326543e-01f,-6.80601e-01f},{-7.592092e-01f,-6.5084666e-01f},{-7.8455657e-01f,-6.200572e-01f},{-8.0865616e-01f,-5.882816e-01f},
{-8.314696e-01f,-5.5557024e-01f},{-8.529606e-01f,-5.219753e-01f},{-8.73095e-01f,-4.8755017e-01f},{-8.918407e-01f,-4.5234957e-01f},
{-9.09168e-01f,-4.1642955e-01f},{-9.2504925e-01f,-3.798472e-01f},{-9.394592e-01f,-3.4266073e-01f},{-9.52375e-01f,-3.0492923e-01f},
{-9.6377605e-01f,-2.6671275e-01f},{-9.7364426e-01f,-2.2807208e-01f},{-9.819639e-01f,-1.8906866e-01f},{-9.8872167e-01f,-1.4976454e-01f},
{-9.93907e-01f,-1.10222206e-01f},{-9.9751145e-01f,-7.0504576e-02f},{-9.995294e-01f,-3.0674804e-02f},{-9.999576e-01f,9.203754e-03f},
{-9.9879545e-01f,4.9067676e-02f},{-9.960447e-01f,8.885355e-02f},{-9.9170977e-01f,1.284981e-01f},{-9.857975e-01f,1.6793829e-01f},
{-9.783174e-01f,2.0711137e-01f},{-9.6928126e-01f,2.4595505e-01f},{-9.5870346e-01f,2.8440753e-01f},{-9.466009e-01f,3.224077e-01f},
{-9.329928e-01f,3.5989505e-01f},{-9.179008e-01f,3.9681e-01f},{-9.013488e-01f,4.3309382e-01f},{-8.8336337e-01f,4.6868882e-01f},
{-8.6397284e-01f,5.0353837e-01f},{-8.4320825e-01f,5.3758705e-01f},{-8.211025e-01f,5.7078075e-01f},{-7.9769087e-01f,6.030666e-01f},
{-7.7301043e-01f,6.343933e-01f},{-7.471006e-01f,6.64711e-01f},{-7.2000253e-01f,6.9397146e-01f},{-6.917592e-01f,7.221282e-01f},
{-6.624158e-01f,7.491364e-01f},{-6.3201874e-01f,7.749531e-01f},{-6.0061646e-01f,7.9953724e-01f},{-5.6825894e-01f,8.228498e-01f},
{-5.3499764e-01f,8.448536e-01f},{-5.0088537e-01f,8.655136e-01f},{-4.659765e-01f,8.847971e-01f},{-4.303265e-01f,9.026733e-01f},
{-3.9399204e-01f,9.191139e-01f},{-3.5703096e-01f,9.340925e-01f},{-3.1950203e-01f,9.475856e-01f},{-2.8146493e-01f,9.5957154e-01f},
{-2.4298018e-01f,9.7003126e-01f},{-2.0410897e-01f,9.789482e-01f},{-1.6491312e-01f,9.863081e-01f},{-1.2545498e-01f,9.920993e-01f},
{-8.579731e-02f,9.963126e-01f},{-4.600318e-02f,9.989413e-01f},{-6.1358847e-03f,9.9998116e-01f},{3.3741172e-02f,9.994306e-01f},
{7.356457e-02f,9.9729043e-01f},{1.1327095e-01f,9.935641e-01f},{1.5279719e-01f,9.882576e-01f},{1.920804e-01f,9.813792e-01f},
{2.310581e-01f,9.7293997e-01f},{2.696683e-01f,9.6295327e-01f},{3.0784965e-01f,9.51435e-01f},{3.4554133e-01f,9.3840355e-01f},
{1.0e+00f,0.0e+00f},{9.9907774e-01f,-4.293826e-02f},{9.963126e-01f,-8.579731e-02f},{9.9170977e-01f,-1.284981e-01f},
{9.8527765e-01f,-1.7096189e-01f},{9.7702813e-01f,-2.1311031e-01f},{9.6697646e-01f,-2.5486565e-01f},{9.551412e-01f,-2.961509e-01f},
{9.4154406e-01f,-3.3688986e-01f},{9.262102e-01f,-3.7700742e-01f},{9.09168e-01f,-4.1642955e-01f},{8.9044875e-01f,-4.5508358e-01f},
{8.7008697e-01f,-4.928982e-01f},{8.4812033e-01f,-5.2980363e-01f},{8.245893e-01f,-5.657318e-01f},{7.9953724e-01f,-6.0061646e-01f},
{7.7301043e-01f,-6.343933e-01f},{7.4505776e-01f,-6.6699994e-01f},{7.1573085e-01f,-6.9837624e-01f},{6.850837e-01f,-7.2846437e-01f},
{6.5317285e-01f,-7.572088e-01f},{6.200572e-01f,-7.8455657e-01f},{5.8579785e-01f,-8.1045717e-01f},{5.5045795e-01f,-8.348629e-01f},
{5.1410276e-01f,-8.577286e-01f},{4.7679922e-01f,-8.790122e-01f},{4.3861625e-01f,-8.986745e-01f},{3.996242e-01f,-9.166791e-01f},
{3.5989505e-01f,-9.329928e-01f},{3.1950203e-01f,-9.475856e-01f},{2.785197e-01f,-9.604305e-01f},{2.370236e-01f,-9.715039e-01f},
{1.9509032e-01f,-9.8078525e-01f},{1.5279719e-01f,-9.882576e-01f},{1.10222206e-01f,-9.93907e-01f},{6.744392e-02f,-9.9772304e-01f},
{2.4541229e-02f,-9.996988e-01f},{-1.840673e-02f,-9.998306e-01f},{-6.1320737e-02f,-9.981181e-01f},{-1.0412163e-01f,-9.945646e-01f},
{-1.4673047e-01f,-9.891765e-01f},{-1.8906866e-01f,-9.819639e-01f},{-2.310581e-01f,-9.7293997e-01f},{-2.7262136e-01f,-9.621214e-01f},
{-3.1368175e-01f,-9.4952816e-01f},{-3.5416353e-01f,-9.351835e-01f},{-3.9399204e-01f,-9.191139e-01f},{-4.3309382e-01f,-9.013488e-01f},
{-4.7139674e-01f,-8.819213e-01f},{-5.0883013e-01f,-8.6086696e-01f},{-5.45325e-01f,-8.382247e-01f},{-5.8081394e-01f,-8.140363e-01f},
{-6.152316e-01f,-7.883464e-01f},{-6.485144e-01f,-7.612024e-01f},{-6.80601e-01f,-7.326543e-01f},{-7.114322e-01f,-7.0275474e-01f},
{-7.409511e-01f,-6.71559e-01f},{-7.6910335e-01f,-6.3912445e-01f},{-7.958369e-01f,-6.0551107e-01f},{-8.211025e-01f,-5.7078075e-01f},
{-8.448536e-01f,-5.3499764e-01f},{-8.6704624e-01f,-4.9822766e-01f},{-8.8763964e-01f,-4.6053872e-01f},{-9.065957e-01f,-4.2200026e-01f},
{-9.238795e-01f,-3.8268343e-01f},{-9.394592e-01f,-3.4266073e-01f},{-9.53306e-01f,-3.0200595e-01f},{-9.6539444e-01f,-2.607941e-01f},
{-9.757021e-01f,-2.1910124e-01f},{-9.842101e-01f,-1.7700422e-01f},{-9.9090266e-01f,-1.345807e-01f},{-9.957674e-01f,-9.1908954e-02f},
{-9.9879545e-01f,-4.9067676e-02f},{-9.9998116e-01f,-6.1358847e-03f},{-9.9932235e-01f,3.6807224e-02f},{-9.968203e-01f,7.968244e-02f},
{-9.9247956e-01f,1.2241068e-01f},{-9.863081e-01f,1.6491312e-01f},{-9.783174e-01f,2.0711137e-01f},{-9.685221e-01f,2.4892761e-01f},
{-9.5694035e-01f,2.9028466e-01f},{-9.4359344e-01f,3.311063e-01f},{-9.285061e-01f,3.713172e-01f},{-9.1170603e-01f,4.1084316e-01f},
{-8.932243e-01f,4.4961134e-01f},{-8.73095e-01f,4.8755017e-01f},{-8.513552e-01f,5.2458966e-01f},{-8.2804507e-01f,5.6066155e-01f},
{-8.032075e-01f,5.956993e-01f},{-7.768885e-01f,6.2963825e-01f},{-7.491364e-01f,6.624158e-01f},{-7.2000253e-01f,6.9397146e-01f},
{-6.8954057e-01f,7.242471e-01f},{-6.578067e-01f,7.531868e-01f},{-6.248595e-01f,7.807372e-01f},{-5.907597e-01f,8.068476e-01f},
{-5.5557024e-01f,8.314696e-01f},{-5.19356e-01f,8.54558e-01f},{-4.8218378e-01f,8.760701e-01f},{-4.4412214e-01f,8.9596623e-01f},
{-4.052413e-01f,9.142098e-01f},{-3.6561298e-01f,9.3076694e-01f},{-3.253103e-01f,9.456073e-01f},{-2.8440753e-01f,9.5870346e-01f},
{-2.4298018e-01f,9.7003126e-01f},{-2.0110464e-01f,9.795698e-01f},{-1.5885815e-01f,9.873014e-01f},{-1.1631863e-01f,9.932119e-01f},
{-7.356457e-02f,9.9729043e-01f},{-3.0674804e-02f,9.995294e-01f},{1.2271538e-02f,9.999247e-01f},{5.5195246e-02f,9.9847555e-01f},
{9.801714e-02f,9.951847e-01f},{1.4065824e-01f,9.900582e-01f},{1.8303989e-01f,9.831055e-01f},{2.2508392e-01f,9.7433937e-01f},
{2.6671275e-01f,9.6377605e-01f},{3.0784965e-01f,9.51435e-01f},{3.4841868e-01f,9.37339e-01f},{3.8834503e-01f,9.2151403e-01f},
{4.2755508e-01f,9.039893e-01f},{4.659765e-01f,8.847971e-01f},{5.0353837e-01f,8.6397284e-01f},{5.4017144e-01f,8.41555e-01f},
{5.7580817e-01f,8.175848e-01f},{6.103828e-01f,7.9210657e-01f},{6.4383155e-01f,7.6516724e-01f},{6.760927e-01f,7.368166e-01f},
{1.0e+00f,0.0e+00f},{9.989413e-01f,-4.600318e-02f},{9.957674e-01f,-9.1908954e-02f},{9.904851e-01f,-1.3762012e-01f},
{9.831055e-01f,-1.8303989e-01f},{9.7364426e-01f,-2.2807208e-01f},{9.621214e-01f,-2.7262136e-01f},{9.485614e-01f,-3.1659338e-01f},
{9.329928e-01f,-3.5989505e-01f},{9.154487e-01f,-4.0243465e-01f},{8.9596623e-01f,-4.4412214e-01f},{8.7458664e-01f,-4.8486924e-01f},
{8.513552e-01f,-5.2458966e-01f},{8.2632107e-01f,-5.6319934e-01f},{7.9953724e-01f,-6.0061646e-01f},{7.710605e-01f,-6.3676184e-01f},
{7.409511e-01f,-6.71559e-01f},{7.092728e-01f,-7.0493406e-01f},{6.760927e-01f,-7.368166e-01f},{6.4148104e-01f,-7.671389e-01f},
{6.0551107e-01f,-7.958369e-01f},{5.6825894e-01f,-8.228498e-01f},{5.2980363e-01f,-8.4812033e-01f},{4.9022648e-01f,-8.715951e-01f},
{4.4961134e-01f,-8.932243e-01f},{4.0804416e-01f,-9.129622e-01f},{3.6561298e-01f,-9.3076694e-01f},{3.224077e-01f,-9.466009e-01f},
{2.785197e-01f,-9.604305e-01f},{2.3404196e-01f,-9.722265e-01f},{1.8906866e-01f,-9.819639e-01f},{1.4369503e-01f,-9.89622e-01f},
{9.801714e-02f,-9.951847e-01f},{5.2131705e-02f,-9.9864024e-01f},{6.1358847e-03f,-9.9998116e-01f},{-3.9872926e-02f,-9.9920475e-01f},
{-8.579731e-02f,-9.963126e-01f},{-1.3154003e-01f,-9.9131083e-01f},{-1.7700422e-01f,-9.842101e-01f},{-2.2209363e-01f,-9.7502536e-01f},
{-2.6671275e-01f,-9.6377605e-01f},{-3.1076714e-01f,-9.5048606e-01f},{-3.5416353e-01f,-9.351835e-01f},{-3.9681e-01f,-9.179008e-01f},
{-4.3861625e-01f,-8.986745e-01f},{-4.7949377e-01f,-8.775453e-01f},{-5.19356e-01f,-8.54558e-01f},{-5.581185e-01f,-8.297612e-01f},
{-5.956993e-01f,-8.032075e-01f},{-6.3201874e-01f,-7.749531e-01f},{-6.6699994e-01f,-7.4505776e-01f},{-7.005688e-01f,-7.1358484e-01f},
{-7.326543e-01f,-6.80601e-01f},{-7.631884e-01f,-6.4617604e-01f},{-7.9210657e-01f,-6.103828e-01f},{-8.193475e-01f,-5.7329714e-01f},
{-8.448536e-01f,-5.3499764e-01f},{-8.685707e-01f,-4.9556527e-01f},{-8.9044875e-01f,-4.5508358e-01f},{-9.104413e-01f,-4.1363832e-01f},
{-9.285061e-01f,-3.713172e-01f},{-9.446048e-01f,-3.2820985e-01f},{-9.5870346e-01f,-2.8440753e-01f},{-9.7077215e-01f,-2.4000302e-01f},
{-9.8078525e-01f,-1.9509032e-01f},{-9.8872167e-01f,-1.4976454e-01f},{-9.945646e-01f,-1.0412163e-01f},{-9.9830157e-01f,-5.8258265e-02f},
{-9.999247e-01f,-1.2271538e-02f},{-9.994306e-01f,3.3741172e-02f},{-9.968203e-01f,7.968244e-02f},{-9.920993e-01f,1.2545498e-01f},
{-9.8527765e-01f,1.7096189e-01f},{-9.7636974e-01f,2.161068e-01f},{-9.6539444e-01f,2.607941e-01f},{-9.52375e-01f,3.0492923e-01f},
{-9.37339e-01f,3.4841868e-01f},{-9.203183e-01f,3.9117038e-01f},{-9.013488e-01f,4.3309382e-01f},{-8.804709e-01f,4.741002e-01f},
{-8.577286e-01f,5.1410276e-01f},{-8.331702e-01f,5.530167e-01f},{-8.068476e-01f,5.907597e-01f},{-7.788165e-01f,6.272518e-01f},
{-7.491364e-01f,6.624158e-01f},{-7.1787006e-01f,6.961771e-01f},{-6.850837e-01f,7.2846437e-01f},{-6.5084666e-01f,7.592092e-01f},
{-6.152316e-01f,7.883464e-01f},{-5.7831377e-01f,8.1581444e-01f},{-5.4017144e-01f,8.41555e-01f},{-5.0088537e-01f,8.655136e-01f},
{-4.6053872e-01f,8.8763964e-01f},{-4.192169e-01f,9.078861e-01f},{-3.7700742e-01f,9.262102e-01f},{-3.3399966e-01f,9.425732e-01f},
{-2.9028466e-01f,9.5694035e-01f},{-2.4595505e-01f,9.6928126e-01f},{-2.0110464e-01f,9.795698e-01f},{-1.558284e-01f,9.8778415e-01f},
{-1.10222206e-01f,9.93907e-01f},{-6.438263e-02f,9.979253e-01f},{-1.840673e-02f,9.998306e-01f},{2.7608145e-02f,9.996188e-01f},
{7.356457e-02f,9.9729043e-01f},{1.19365215e-01f,9.928504e-01f},{1.6491312e-01f,9.863081e-01f},{2.1011184e-01f,9.7767735e-01f},
{2.5486565e-01f,9.6697646e-01f},{2.9907984e-01f,9.542281e-01f},{3.4266073e-01f,9.394592e-01f},{3.8551605e-01f,9.227011e-01f},
{4.2755508e-01f,9.039893e-01f},{4.6868882e-01f,8.8336337e-01f},{5.0883013e-01f,8.6086696e-01f},{5.4789406e-01f,8.3654773e-01f},
{5.8579785e-01f,8.1045717e-01f},{6.2246126e-01f,7.826506e-01f},{6.578067e-01f,7.531868e-01f},{6.917592e-01f,7.221282e-01f},
{7.242471e-01f,6.8954057e-01f},{7.552014e-01f,6.5549284e-01f},{7.8455657e-01f,6.200572e-01f},{8.122506e-01f,5.8330864e-01f},
{8.382247e-01f,5.45325e-01f},{8.6242396e-01f,5.0618666e-01f},{8.847971e-01f,4.659765e-01f},{9.0529674e-01f,4.2477968e-01f},
};
__device__ const float2 TWB128[128] = {
{1.0e+00f,0.0e+00f},{1.0e+00f,0.0e+00f},{1.0e+00f,0.0e+00f},{1.0e+00f,0.0e+00f},
{1.0e+00f,0.0e+00f},{1.0e+00f,0.0e+00f},{1.0e+00f,0.0e+00f},{1.0e+00f,0.0e+00f},
{1.0e+00f,0.0e+00f},{9.9879545e-01f,-4.9067676e-02f},{9.951847e-01f,-9.801714e-02f},{9.891765e-01f,-1.4673047e-01f},
{9.8078525e-01f,-1.9509032e-01f},{9.7003126e-01f,-2.4298018e-01f},{9.5694035e-01f,-2.9028466e-01f},{9.4154406e-01f,-3.3688986e-01f},
{1.0e+00f,0.0e+00f},{9.951847e-01f,-9.801714e-02f},{9.8078525e-01f,-1.9509032e-01f},{9.5694035e-01f,-2.9028466e-01f},
{9.238795e-01f,-3.8268343e-01f},{8.819213e-01f,-4.7139674e-01f},{8.314696e-01f,-5.5557024e-01f},{7.7301043e-01f,-6.343933e-01f},
{1.0e+00f,0.0e+00f},{9.891765e-01f,-1.4673047e-01f},{9.5694035e-01f,-2.9028466e-01f},{9.039893e-01f,-4.2755508e-01f},
{8.314696e-01f,-5.5557024e-01f},{7.409511e-01f,-6.71559e-01f},{6.343933e-01f,-7.7301043e-01f},{5.1410276e-01f,-8.577286e-01f},
{1.0e+00f,0.0e+00f},{9.8078525e-01f,-1.9509032e-01f},{9.238795e-01f,-3.8268343e-01f},{8.314696e-01f,-5.5557024e-01f},
{7.0710677e-01f,-7.0710677e-01f},{5.5557024e-01f,-8.314696e-01f},{3.8268343e-01f,-9.238795e-01f},{1.9509032e-01f,-9.8078525e-01f},
{1.0e+00f,0.0e+00f},{9.7003126e-01f,-2.4298018e-01f},{8.819213e-01f,-4.7139674e-01f},{7.409511e-01f,-6.71559e-01f},
{5.5557024e-01f,-8.314696e-01f},{3.3688986e-01f,-9.4154406e-01f},{9.801714e-02f,-9.951847e-01f},{-1.4673047e-01f,-9.891765e-01f},
{1.0e+00f,0.0e+00f},{9.5694035e-01f,-2.9028466e-01f},{8.314696e-01f,-5.5557024e-01f},{6.343933e-01f,-7.7301043e-01f},
{3.8268343e-01f,-9.238795e-01f},{9.801714e-02f,-9.951847e-01f},{-1.9509032e-01f,-9.8078525e-01f},{-4.7139674e-01f,-8.819213e-01f},
{1.0e+00f,0.0e+00f},{9.4154406e-01f,-3.3688986e-01f},{7.7301043e-01f,-6.343933e-01f},{5.1410276e-01f,-8.577286e-01f},
{1.9509032e-01f,-9.8078525e-01f},{-1.4673047e-01f,-9.891765e-01f},{-4.7139674e-01f,-8.819213e-01f},{-7.409511e-01f,-6.71559e-01f},
{1.0e+00f,0.0e+00f},{9.238795e-01f,-3.8268343e-01f},{7.0710677e-01f,-7.0710677e-01f},{3.8268343e-01f,-9.238795e-01f},
{6.123234e-17f,-1.0e+00f},{-3.8268343e-01f,-9.238795e-01f},{-7.0710677e-01f,-7.0710677e-01f},{-9.238795e-01f,-3.8268343e-01f},
{1.0e+00f,0.0e+00f},{9.039893e-01f,-4.2755508e-01f},{6.343933e-01f,-7.7301043e-01f},{2.4298018e-01f,-9.7003126e-01f},
{-1.9509032e-01f,-9.8078525e-01f},{-5.956993e-01f,-8.032075e-01f},{-8.819213e-01f,-4.7139674e-01f},{-9.9879545e-01f,-4.9067676e-02f},
{1.0e+00f,0.0e+00f},{8.819213e-01f,-4.7139674e-01f},{5.5557024e-01f,-8.314696e-01f},{9.801714e-02f,-9.951847e-01f},
{-3.8268343e-01f,-9.238795e-01f},{-7.7301043e-01f,-6.343933e-01f},{-9.8078525e-01f,-1.9509032e-01f},{-9.5694035e-01f,2.9028466e-01f},
{1.0e+00f,0.0e+00f},{8.577286e-01f,-5.1410276e-01f},{4.7139674e-01f,-8.819213e-01f},{-4.9067676e-02f,-9.9879545e-01f},
{-5.5557024e-01f,-8.314696e-01f},{-9.039893e-01f,-4.2755508e-01f},{-9.951847e-01f,9.801714e-02f},{-8.032075e-01f,5.956993e-01f},
{1.0e+00f,0.0e+00f},{8.314696e-01f,-5.5557024e-01f},{3.8268343e-01f,-9.238795e-01f},{-1.9509032e-01f,-9.8078525e-01f},
{-7.0710677e-01f,-7.0710677e-01f},{-9.8078525e-01f,-1.9509032e-01f},{-9.238795e-01f,3.8268343e-01f},{-5.5557024e-01f,8.314696e-01f},
{1.0e+00f,0.0e+00f},{8.032075e-01f,-5.956993e-01f},{2.9028466e-01f,-9.5694035e-01f},{-3.3688986e-01f,-9.4154406e-01f},
{-8.314696e-01f,-5.5557024e-01f},{-9.9879545e-01f,4.9067676e-02f},{-7.7301043e-01f,6.343933e-01f},{-2.4298018e-01f,9.7003126e-01f},
{1.0e+00f,0.0e+00f},{7.7301043e-01f,-6.343933e-01f},{1.9509032e-01f,-9.8078525e-01f},{-4.7139674e-01f,-8.819213e-01f},
{-9.238795e-01f,-3.8268343e-01f},{-9.5694035e-01f,2.9028466e-01f},{-5.5557024e-01f,8.314696e-01f},{9.801714e-02f,9.951847e-01f},
{1.0e+00f,0.0e+00f},{7.409511e-01f,-6.71559e-01f},{9.801714e-02f,-9.951847e-01f},{-5.956993e-01f,-8.032075e-01f},
{-9.8078525e-01f,-1.9509032e-01f},{-8.577286e-01f,5.1410276e-01f},{-2.9028466e-01f,9.5694035e-01f},{4.2755508e-01f,9.039893e-01f},
};
__device__ const float2 TWA448[448] = {
{1.0e+00f,0.0e+00f},{1.0e+00f,0.0e+00f},{1.0e+00f,0.0e+00f},{1.0e+00f,0.0e+00f},
{1.0e+00f,0.0e+00f},{1.0e+00f,0.0e+00f},{1.0e+00f,0.0e+00f},{1.0e+00f,0.0e+00f},
{1.0e+00f,0.0e+00f},{1.0e+00f,0.0e+00f},{1.0e+00f,0.0e+00f},{1.0e+00f,0.0e+00f},
{1.0e+00f,0.0e+00f},{1.0e+00f,0.0e+00f},{1.0e+00f,0.0e+00f},{1.0e+00f,0.0e+00f},
{1.0e+00f,0.0e+00f},{1.0e+00f,0.0e+00f},{1.0e+00f,0.0e+00f},{1.0e+00f,0.0e+00f},
{1.0e+00f,0.0e+00f},{1.0e+00f,0.0e+00f},{1.0e+00f,0.0e+00f},{1.0e+00f,0.0e+00f},
{1.0e+00f,0.0e+00f},{1.0e+00f,0.0e+00f},{1.0e+00f,0.0e+00f},{1.0e+00f,0.0e+00f},
{1.0e+00f,0.0e+00f},{1.0e+00f,0.0e+00f},{1.0e+00f,0.0e+00f},{1.0e+00f,0.0e+00f},
{1.0e+00f,0.0e+00f},{1.0e+00f,0.0e+00f},{1.0e+00f,0.0e+00f},{1.0e+00f,0.0e+00f},
{1.0e+00f,0.0e+00f},{1.0e+00f,0.0e+00f},{1.0e+00f,0.0e+00f},{1.0e+00f,0.0e+00f},
{1.0e+00f,0.0e+00f},{1.0e+00f,0.0e+00f},{1.0e+00f,0.0e+00f},{1.0e+00f,0.0e+00f},
{1.0e+00f,0.0e+00f},{1.0e+00f,0.0e+00f},{1.0e+00f,0.0e+00f},{1.0e+00f,0.0e+00f},
{1.0e+00f,0.0e+00f},{1.0e+00f,0.0e+00f},{1.0e+00f,0.0e+00f},{1.0e+00f,0.0e+00f},
{1.0e+00f,0.0e+00f},{1.0e+00f,0.0e+00f},{1.0e+00f,0.0e+00f},{1.0e+00f,0.0e+00f},
{1.0e+00f,0.0e+00f},{9.9990165e-01f,-1.4024507e-02f},{9.996066e-01f,-2.8046256e-02f},{9.99115e-01f,-4.2062487e-02f},
{9.984268e-01f,-5.6070447e-02f},{9.9754226e-01f,-7.0067376e-02f},{9.964615e-01f,-8.405052e-02f},{9.951847e-01f,-9.801714e-02f},
{9.937122e-01f,-1.1196448e-01f},{9.920442e-01f,-1.258898e-01f},{9.9018115e-01f,-1.3979034e-01f},{9.8812324e-01f,-1.536634e-01f},
{9.85871e-01f,-1.6750622e-01f},{9.8342484e-01f,-1.8131611e-01f},{9.8078525e-01f,-1.9509032e-01f},{9.779528e-01f,-2.0882617e-01f},
{9.749279e-01f,-2.2252093e-01f},{9.717113e-01f,-2.3617193e-01f},{9.683035e-01f,-2.4977648e-01f},{9.647053e-01f,-2.633319e-01f},
{9.609173e-01f,-2.768355e-01f},{9.5694035e-01f,-2.9028466e-01f},{9.527751e-01f,-3.0367675e-01f},{9.484225e-01f,-3.170091e-01f},
{9.4388336e-01f,-3.3027905e-01f},{9.391585e-01f,-3.4348407e-01f},{9.342489e-01f,-3.5662153e-01f},{9.291556e-01f,-3.6968884e-01f},
{9.238795e-01f,-3.8268343e-01f},{9.1842175e-01f,-3.9560276e-01f},{9.1278327e-01f,-4.0844426e-01f},{9.0696526e-01f,-4.2120543e-01f},
{9.0096885e-01f,-4.3388373e-01f},{8.9479524e-01f,-4.464767e-01f},{8.884456e-01f,-4.5898187e-01f},{8.819213e-01f,-4.7139674e-01f},
{8.752234e-01f,-4.837189e-01f},{8.683534e-01f,-4.959459e-01f},{8.613126e-01f,-5.0807536e-01f},{8.5410243e-01f,-5.201049e-01f},
{8.467242e-01f,-5.320321e-01f},{8.3917946e-01f,-5.4385465e-01f},{8.314696e-01f,-5.5557024e-01f},{8.2359624e-01f,-5.671765e-01f},
{8.155609e-01f,-5.786713e-01f},{8.0736506e-01f,-5.9005225e-01f},{7.9901046e-01f,-6.013171e-01f},{7.9049873e-01f,-6.1246365e-01f},
{7.818315e-01f,-6.234898e-01f},{7.7301043e-01f,-6.343933e-01f},{7.640374e-01f,-6.45172e-01f},{7.54914e-01f,-6.5582377e-01f},
{7.456422e-01f,-6.6634655e-01f},{7.3622364e-01f,-6.767383e-01f},{7.266603e-01f,-6.8699694e-01f},{7.1695405e-01f,-6.971204e-01f},
{1.0e+00f,0.0e+00f},{9.996066e-01f,-2.8046256e-02f},{9.984268e-01f,-5.6070447e-02f},{9.964615e-01f,-8.405052e-02f},
{9.937122e-01f,-1.1196448e-01f},{9.9018115e-01f,-1.3979034e-01f},{9.85871e-01f,-1.6750622e-01f},{9.8078525e-01f,-1.9509032e-01f},
{9.749279e-01f,-2.2252093e-01f},{9.683035e-01f,-2.4977648e-01f},{9.609173e-01f,-2.768355e-01f},{9.527751e-01f,-3.0367675e-01f},
{9.4388336e-01f,-3.3027905e-01f},{9.342489e-01f,-3.5662153e-01f},{9.238795e-01f,-3.8268343e-01f},{9.1278327e-01f,-4.0844426e-01f},
{9.0096885e-01f,-4.3388373e-01f},{8.884456e-01f,-4.5898187e-01f},{8.752234e-01f,-4.837189e-01f},{8.613126e-01f,-5.0807536e-01f},
{8.467242e-01f,-5.320321e-01f},{8.314696e-01f,-5.5557024e-01f},{8.155609e-01f,-5.786713e-01f},{7.9901046e-01f,-6.013171e-01f},
{7.818315e-01f,-6.234898e-01f},{7.640374e-01f,-6.45172e-01f},{7.456422e-01f,-6.6634655e-01f},{7.266603e-01f,-6.8699694e-01f},
{7.0710677e-01f,-7.0710677e-01f},{6.8699694e-01f,-7.266603e-01f},{6.6634655e-01f,-7.456422e-01f},{6.45172e-01f,-7.640374e-01f},
{6.234898e-01f,-7.818315e-01f},{6.013171e-01f,-7.9901046e-01f},{5.786713e-01f,-8.155609e-01f},{5.5557024e-01f,-8.314696e-01f},
{5.320321e-01f,-8.467242e-01f},{5.0807536e-01f,-8.613126e-01f},{4.837189e-01f,-8.752234e-01f},{4.5898187e-01f,-8.884456e-01f},
{4.3388373e-01f,-9.0096885e-01f},{4.0844426e-01f,-9.1278327e-01f},{3.8268343e-01f,-9.238795e-01f},{3.5662153e-01f,-9.342489e-01f},
{3.3027905e-01f,-9.4388336e-01f},{3.0367675e-01f,-9.527751e-01f},{2.768355e-01f,-9.609173e-01f},{2.4977648e-01f,-9.683035e-01f},
{2.2252093e-01f,-9.749279e-01f},{1.9509032e-01f,-9.8078525e-01f},{1.6750622e-01f,-9.85871e-01f},{1.3979034e-01f,-9.9018115e-01f},
{1.1196448e-01f,-9.937122e-01f},{8.405052e-02f,-9.964615e-01f},{5.6070447e-02f,-9.984268e-01f},{2.8046256e-02f,-9.996066e-01f},
{1.0e+00f,0.0e+00f},{9.99115e-01f,-4.2062487e-02f},{9.964615e-01f,-8.405052e-02f},{9.920442e-01f,-1.258898e-01f},
{9.85871e-01f,-1.6750622e-01f},{9.779528e-01f,-2.0882617e-01f},{9.683035e-01f,-2.4977648e-01f},{9.5694035e-01f,-2.9028466e-01f},
{9.4388336e-01f,-3.3027905e-01f},{9.291556e-01f,-3.6968884e-01f},{9.1278327e-01f,-4.0844426e-01f},{8.9479524e-01f,-4.464767e-01f},
{8.752234e-01f,-4.837189e-01f},{8.5410243e-01f,-5.201049e-01f},{8.314696e-01f,-5.5557024e-01f},{8.0736506e-01f,-5.9005225e-01f},
{7.818315e-01f,-6.234898e-01f},{7.54914e-01f,-6.5582377e-01f},{7.266603e-01f,-6.8699694e-01f},{6.971204e-01f,-7.1695405e-01f},
{6.6634655e-01f,-7.456422e-01f},{6.343933e-01f,-7.7301043e-01f},{6.013171e-01f,-7.9901046e-01f},{5.671765e-01f,-8.2359624e-01f},
{5.320321e-01f,-8.467242e-01f},{4.959459e-01f,-8.683534e-01f},{4.5898187e-01f,-8.884456e-01f},{4.2120543e-01f,-9.0696526e-01f},
{3.8268343e-01f,-9.238795e-01f},{3.4348407e-01f,-9.391585e-01f},{3.0367675e-01f,-9.527751e-01f},{2.633319e-01f,-9.647053e-01f},
{2.2252093e-01f,-9.749279e-01f},{1.8131611e-01f,-9.8342484e-01f},{1.3979034e-01f,-9.9018115e-01f},{9.801714e-02f,-9.951847e-01f},
{5.6070447e-02f,-9.984268e-01f},{1.4024507e-02f,-9.9990165e-01f},{-2.8046256e-02f,-9.996066e-01f},{-7.0067376e-02f,-9.9754226e-01f},
{-1.1196448e-01f,-9.937122e-01f},{-1.536634e-01f,-9.8812324e-01f},{-1.9509032e-01f,-9.8078525e-01f},{-2.3617193e-01f,-9.717113e-01f},
{-2.768355e-01f,-9.609173e-01f},{-3.170091e-01f,-9.484225e-01f},{-3.5662153e-01f,-9.342489e-01f},{-3.9560276e-01f,-9.1842175e-01f},
{-4.3388373e-01f,-9.0096885e-01f},{-4.7139674e-01f,-8.819213e-01f},{-5.0807536e-01f,-8.613126e-01f},{-5.4385465e-01f,-8.3917946e-01f},
{-5.786713e-01f,-8.155609e-01f},{-6.1246365e-01f,-7.9049873e-01f},{-6.45172e-01f,-7.640374e-01f},{-6.767383e-01f,-7.3622364e-01f},
{1.0e+00f,0.0e+00f},{9.984268e-01f,-5.6070447e-02f},{9.937122e-01f,-1.1196448e-01f},{9.85871e-01f,-1.6750622e-01f},
{9.749279e-01f,-2.2252093e-01f},{9.609173e-01f,-2.768355e-01f},{9.4388336e-01f,-3.3027905e-01f},{9.238795e-01f,-3.8268343e-01f},
{9.0096885e-01f,-4.3388373e-01f},{8.752234e-01f,-4.837189e-01f},{8.467242e-01f,-5.320321e-01f},{8.155609e-01f,-5.786713e-01f},
{7.818315e-01f,-6.234898e-01f},{7.456422e-01f,-6.6634655e-01f},{7.0710677e-01f,-7.0710677e-01f},{6.6634655e-01f,-7.456422e-01f},
{6.234898e-01f,-7.818315e-01f},{5.786713e-01f,-8.155609e-01f},{5.320321e-01f,-8.467242e-01f},{4.837189e-01f,-8.752234e-01f},
{4.3388373e-01f,-9.0096885e-01f},{3.8268343e-01f,-9.238795e-01f},{3.3027905e-01f,-9.4388336e-01f},{2.768355e-01f,-9.609173e-01f},
{2.2252093e-01f,-9.749279e-01f},{1.6750622e-01f,-9.85871e-01f},{1.1196448e-01f,-9.937122e-01f},{5.6070447e-02f,-9.984268e-01f},
{6.123234e-17f,-1.0e+00f},{-5.6070447e-02f,-9.984268e-01f},{-1.1196448e-01f,-9.937122e-01f},{-1.6750622e-01f,-9.85871e-01f},
{-2.2252093e-01f,-9.749279e-01f},{-2.768355e-01f,-9.609173e-01f},{-3.3027905e-01f,-9.4388336e-01f},{-3.8268343e-01f,-9.238795e-01f},
{-4.3388373e-01f,-9.0096885e-01f},{-4.837189e-01f,-8.752234e-01f},{-5.320321e-01f,-8.467242e-01f},{-5.786713e-01f,-8.155609e-01f},
{-6.234898e-01f,-7.818315e-01f},{-6.6634655e-01f,-7.456422e-01f},{-7.0710677e-01f,-7.0710677e-01f},{-7.456422e-01f,-6.6634655e-01f},
{-7.818315e-01f,-6.234898e-01f},{-8.155609e-01f,-5.786713e-01f},{-8.467242e-01f,-5.320321e-01f},{-8.752234e-01f,-4.837189e-01f},
{-9.0096885e-01f,-4.3388373e-01f},{-9.238795e-01f,-3.8268343e-01f},{-9.4388336e-01f,-3.3027905e-01f},{-9.609173e-01f,-2.768355e-01f},
{-9.749279e-01f,-2.2252093e-01f},{-9.85871e-01f,-1.6750622e-01f},{-9.937122e-01f,-1.1196448e-01f},{-9.984268e-01f,-5.6070447e-02f},
{1.0e+00f,0.0e+00f},{9.9754226e-01f,-7.0067376e-02f},{9.9018115e-01f,-1.3979034e-01f},{9.779528e-01f,-2.0882617e-01f},
{9.609173e-01f,-2.768355e-01f},{9.391585e-01f,-3.4348407e-01f},{9.1278327e-01f,-4.0844426e-01f},{8.819213e-01f,-4.7139674e-01f},
{8.467242e-01f,-5.320321e-01f},{8.0736506e-01f,-5.9005225e-01f},{7.640374e-01f,-6.45172e-01f},{7.1695405e-01f,-6.971204e-01f},
{6.6634655e-01f,-7.456422e-01f},{6.1246365e-01f,-7.9049873e-01f},{5.5557024e-01f,-8.314696e-01f},{4.959459e-01f,-8.683534e-01f},
{4.3388373e-01f,-9.0096885e-01f},{3.6968884e-01f,-9.291556e-01f},{3.0367675e-01f,-9.527751e-01f},{2.3617193e-01f,-9.717113e-01f},
{1.6750622e-01f,-9.85871e-01f},{9.801714e-02f,-9.951847e-01f},{2.8046256e-02f,-9.996066e-01f},{-4.2062487e-02f,-9.99115e-01f},
{-1.1196448e-01f,-9.937122e-01f},{-1.8131611e-01f,-9.8342484e-01f},{-2.4977648e-01f,-9.683035e-01f},{-3.170091e-01f,-9.484225e-01f},
{-3.8268343e-01f,-9.238795e-01f},{-4.464767e-01f,-8.9479524e-01f},{-5.0807536e-01f,-8.613126e-01f},{-5.671765e-01f,-8.2359624e-01f},
{-6.234898e-01f,-7.818315e-01f},{-6.767383e-01f,-7.3622364e-01f},{-7.266603e-01f,-6.8699694e-01f},{-7.7301043e-01f,-6.343933e-01f},
{-8.155609e-01f,-5.786713e-01f},{-8.5410243e-01f,-5.201049e-01f},{-8.884456e-01f,-4.5898187e-01f},{-9.1842175e-01f,-3.9560276e-01f},
{-9.4388336e-01f,-3.3027905e-01f},{-9.647053e-01f,-2.633319e-01f},{-9.8078525e-01f,-1.9509032e-01f},{-9.920442e-01f,-1.258898e-01f},
{-9.984268e-01f,-5.6070447e-02f},{-9.9990165e-01f,1.4024507e-02f},{-9.964615e-01f,8.405052e-02f},{-9.8812324e-01f,1.536634e-01f},
{-9.749279e-01f,2.2252093e-01f},{-9.5694035e-01f,2.9028466e-01f},{-9.342489e-01f,3.5662153e-01f},{-9.0696526e-01f,4.2120543e-01f},
{-8.752234e-01f,4.837189e-01f},{-8.3917946e-01f,5.4385465e-01f},{-7.9901046e-01f,6.013171e-01f},{-7.54914e-01f,6.5582377e-01f},
{1.0e+00f,0.0e+00f},{9.964615e-01f,-8.405052e-02f},{9.85871e-01f,-1.6750622e-01f},{9.683035e-01f,-2.4977648e-01f},
{9.4388336e-01f,-3.3027905e-01f},{9.1278327e-01f,-4.0844426e-01f},{8.752234e-01f,-4.837189e-01f},{8.314696e-01f,-5.5557024e-01f},
{7.818315e-01f,-6.234898e-01f},{7.266603e-01f,-6.8699694e-01f},{6.6634655e-01f,-7.456422e-01f},{6.013171e-01f,-7.9901046e-01f},
{5.320321e-01f,-8.467242e-01f},{4.5898187e-01f,-8.884456e-01f},{3.8268343e-01f,-9.238795e-01f},{3.0367675e-01f,-9.527751e-01f},
{2.2252093e-01f,-9.749279e-01f},{1.3979034e-01f,-9.9018115e-01f},{5.6070447e-02f,-9.984268e-01f},{-2.8046256e-02f,-9.996066e-01f},
{-1.1196448e-01f,-9.937122e-01f},{-1.9509032e-01f,-9.8078525e-01f},{-2.768355e-01f,-9.609173e-01f},{-3.5662153e-01f,-9.342489e-01f},
{-4.3388373e-01f,-9.0096885e-01f},{-5.0807536e-01f,-8.613126e-01f},{-5.786713e-01f,-8.155609e-01f},{-6.45172e-01f,-7.640374e-01f},
{-7.0710677e-01f,-7.0710677e-01f},{-7.640374e-01f,-6.45172e-01f},{-8.155609e-01f,-5.786713e-01f},{-8.613126e-01f,-5.0807536e-01f},
{-9.0096885e-01f,-4.3388373e-01f},{-9.342489e-01f,-3.5662153e-01f},{-9.609173e-01f,-2.768355e-01f},{-9.8078525e-01f,-1.9509032e-01f},
{-9.937122e-01f,-1.1196448e-01f},{-9.996066e-01f,-2.8046256e-02f},{-9.984268e-01f,5.6070447e-02f},{-9.9018115e-01f,1.3979034e-01f},
{-9.749279e-01f,2.2252093e-01f},{-9.527751e-01f,3.0367675e-01f},{-9.238795e-01f,3.8268343e-01f},{-8.884456e-01f,4.5898187e-01f},
{-8.467242e-01f,5.320321e-01f},{-7.9901046e-01f,6.013171e-01f},{-7.456422e-01f,6.6634655e-01f},{-6.8699694e-01f,7.266603e-01f},
{-6.234898e-01f,7.818315e-01f},{-5.5557024e-01f,8.314696e-01f},{-4.837189e-01f,8.752234e-01f},{-4.0844426e-01f,9.1278327e-01f},
{-3.3027905e-01f,9.4388336e-01f},{-2.4977648e-01f,9.683035e-01f},{-1.6750622e-01f,9.85871e-01f},{-8.405052e-02f,9.964615e-01f},
{1.0e+00f,0.0e+00f},{9.951847e-01f,-9.801714e-02f},{9.8078525e-01f,-1.9509032e-01f},{9.5694035e-01f,-2.9028466e-01f},
{9.238795e-01f,-3.8268343e-01f},{8.819213e-01f,-4.7139674e-01f},{8.314696e-01f,-5.5557024e-01f},{7.7301043e-01f,-6.343933e-01f},
{7.0710677e-01f,-7.0710677e-01f},{6.343933e-01f,-7.7301043e-01f},{5.5557024e-01f,-8.314696e-01f},{4.7139674e-01f,-8.819213e-01f},
{3.8268343e-01f,-9.238795e-01f},{2.9028466e-01f,-9.5694035e-01f},{1.9509032e-01f,-9.8078525e-01f},{9.801714e-02f,-9.951847e-01f},
{6.123234e-17f,-1.0e+00f},{-9.801714e-02f,-9.951847e-01f},{-1.9509032e-01f,-9.8078525e-01f},{-2.9028466e-01f,-9.5694035e-01f},
{-3.8268343e-01f,-9.238795e-01f},{-4.7139674e-01f,-8.819213e-01f},{-5.5557024e-01f,-8.314696e-01f},{-6.343933e-01f,-7.7301043e-01f},
{-7.0710677e-01f,-7.0710677e-01f},{-7.7301043e-01f,-6.343933e-01f},{-8.314696e-01f,-5.5557024e-01f},{-8.819213e-01f,-4.7139674e-01f},
{-9.238795e-01f,-3.8268343e-01f},{-9.5694035e-01f,-2.9028466e-01f},{-9.8078525e-01f,-1.9509032e-01f},{-9.951847e-01f,-9.801714e-02f},
{-1.0e+00f,-1.2246469e-16f},{-9.951847e-01f,9.801714e-02f},{-9.8078525e-01f,1.9509032e-01f},{-9.5694035e-01f,2.9028466e-01f},
{-9.238795e-01f,3.8268343e-01f},{-8.819213e-01f,4.7139674e-01f},{-8.314696e-01f,5.5557024e-01f},{-7.7301043e-01f,6.343933e-01f},
{-7.0710677e-01f,7.0710677e-01f},{-6.343933e-01f,7.7301043e-01f},{-5.5557024e-01f,8.314696e-01f},{-4.7139674e-01f,8.819213e-01f},
{-3.8268343e-01f,9.238795e-01f},{-2.9028466e-01f,9.5694035e-01f},{-1.9509032e-01f,9.8078525e-01f},{-9.801714e-02f,9.951847e-01f},
{-1.8369701e-16f,1.0e+00f},{9.801714e-02f,9.951847e-01f},{1.9509032e-01f,9.8078525e-01f},{2.9028466e-01f,9.5694035e-01f},
{3.8268343e-01f,9.238795e-01f},{4.7139674e-01f,8.819213e-01f},{5.5557024e-01f,8.314696e-01f},{6.343933e-01f,7.7301043e-01f},
};
__device__ const float2 TWB56[56] = {
{1.0e+00f,0.0e+00f},{1.0e+00f,0.0e+00f},{1.0e+00f,0.0e+00f},{1.0e+00f,0.0e+00f},
{1.0e+00f,0.0e+00f},{1.0e+00f,0.0e+00f},{1.0e+00f,0.0e+00f},{1.0e+00f,0.0e+00f},
{9.937122e-01f,-1.1196448e-01f},{9.749279e-01f,-2.2252093e-01f},{9.4388336e-01f,-3.3027905e-01f},{9.0096885e-01f,-4.3388373e-01f},
{8.467242e-01f,-5.320321e-01f},{7.818315e-01f,-6.234898e-01f},{1.0e+00f,0.0e+00f},{9.749279e-01f,-2.2252093e-01f},
{9.0096885e-01f,-4.3388373e-01f},{7.818315e-01f,-6.234898e-01f},{6.234898e-01f,-7.818315e-01f},{4.3388373e-01f,-9.0096885e-01f},
{2.2252093e-01f,-9.749279e-01f},{1.0e+00f,0.0e+00f},{9.4388336e-01f,-3.3027905e-01f},{7.818315e-01f,-6.234898e-01f},
{5.320321e-01f,-8.467242e-01f},{2.2252093e-01f,-9.749279e-01f},{-1.1196448e-01f,-9.937122e-01f},{-4.3388373e-01f,-9.0096885e-01f},
{1.0e+00f,0.0e+00f},{9.0096885e-01f,-4.3388373e-01f},{6.234898e-01f,-7.818315e-01f},{2.2252093e-01f,-9.749279e-01f},
{-2.2252093e-01f,-9.749279e-01f},{-6.234898e-01f,-7.818315e-01f},{-9.0096885e-01f,-4.3388373e-01f},{1.0e+00f,0.0e+00f},
{8.467242e-01f,-5.320321e-01f},{4.3388373e-01f,-9.0096885e-01f},{-1.1196448e-01f,-9.937122e-01f},{-6.234898e-01f,-7.818315e-01f},
{-9.4388336e-01f,-3.3027905e-01f},{-9.749279e-01f,2.2252093e-01f},{1.0e+00f,0.0e+00f},{7.818315e-01f,-6.234898e-01f},
{2.2252093e-01f,-9.749279e-01f},{-4.3388373e-01f,-9.0096885e-01f},{-9.0096885e-01f,-4.3388373e-01f},{-9.749279e-01f,2.2252093e-01f},
{-6.234898e-01f,7.818315e-01f},{1.0e+00f,0.0e+00f},{7.0710677e-01f,-7.0710677e-01f},{6.123234e-17f,-1.0e+00f},
{-7.0710677e-01f,-7.0710677e-01f},{-1.0e+00f,-1.2246469e-16f},{-7.0710677e-01f,7.0710677e-01f},{-1.8369701e-16f,1.0e+00f},
};

__device__ __align__(1024) unsigned char g_KV[SEQ * 128];
__device__ __align__(16) __nv_bfloat16 g_O[SEQ * DM];
__device__ __align__(16) unsigned int g_Wt[DF * SEQ];
__device__ __align__(16) float2 g_T[DF * SEQ];

__device__ __forceinline__ uint32_t smem_u32(const void* p) { return (uint32_t)__cvta_generic_to_shared(p); }

__device__ __forceinline__ void mbar_init(uint32_t bar, uint32_t count) {
    asm volatile("mbarrier.init.shared::cta.b64 [%0], %1;\n" ::"r"(bar), "r"(count) : "memory");
}
__device__ __forceinline__ void mbar_expect_tx(uint32_t bar, uint32_t bytes) {
    asm volatile("mbarrier.arrive.expect_tx.shared::cta.b64 _, [%0], %1;\n" ::"r"(bar), "r"(bytes) : "memory");
}
__device__ __forceinline__ void mbar_arrive(uint32_t bar) {
    asm volatile("mbarrier.arrive.shared::cta.b64 _, [%0];\n" ::"r"(bar) : "memory");
}
__device__ __forceinline__ void mbar_wait(uint32_t bar, uint32_t parity) {
    asm volatile(
        "{\n"
        ".reg .pred P1;\n"
        "LAB_WAIT:\n"
        "mbarrier.try_wait.parity.shared::cta.b64 P1, [%0], %1;\n"
        "@P1 bra DONE;\n"
        "bra LAB_WAIT;\n"
        "DONE:\n"
        "}\n" ::"r"(bar), "r"(parity) : "memory");
}
__device__ __forceinline__ void bulk_g2s(uint32_t dst, const void* src, uint32_t bytes, uint32_t bar) {
    asm volatile("cp.async.bulk.shared::cluster.global.mbarrier::complete_tx::bytes [%0], [%1], %2, [%3];\n" ::"r"(dst),
                 "l"(src), "r"(bytes), "r"(bar)
                 : "memory");
}
__device__ __forceinline__ void tma_2d(uint32_t dst, const CUtensorMap* map, int c0, int c1, uint32_t bar) {
    asm volatile("cp.async.bulk.tensor.2d.shared::cluster.global.mbarrier::complete_tx::bytes [%0], [%1, {%3, %4}], [%2];\n" ::"r"(dst),
                 "l"(map), "r"(bar), "r"(c0), "r"(c1)
                 : "memory");
}
__device__ __forceinline__ void cp_async16(uint32_t dst, const void* src) {
    asm volatile("cp.async.cg.shared.global [%0], [%1], 16;\n" ::"r"(dst), "l"(src) : "memory");
}
__device__ __forceinline__ void cp_async8(uint32_t dst, const void* src) {
    asm volatile("cp.async.ca.shared.global [%0], [%1], 8;\n" ::"r"(dst), "l"(src) : "memory");
}
__device__ __forceinline__ void cp_async_commit() { asm volatile("cp.async.commit_group;\n" ::: "memory"); }
template <int N>
__device__ __forceinline__ void cp_async_wait() { asm volatile("cp.async.wait_group %0;\n" ::"n"(N) : "memory"); }

__device__ __forceinline__ uint32_t pack_bf16(float lo, float hi) {
    uint32_t r;
    asm("cvt.rn.bf16x2.f32 %0, %1, %2;\n" : "=r"(r) : "f"(hi), "f"(lo));
    return r;
}
__device__ __forceinline__ float ex2(float x) {
    float y;
    asm("ex2.approx.ftz.f32 %0, %1;\n" : "=f"(y) : "f"(x));
    return y;
}
__device__ __forceinline__ void wgmma_fence() { asm volatile("wgmma.fence.sync.aligned;\n" ::: "memory"); }
__device__ __forceinline__ void wgmma_commit() { asm volatile("wgmma.commit_group.sync.aligned;\n" ::: "memory"); }
template <int N>
__device__ __forceinline__ void wgmma_wait() { asm volatile("wgmma.wait_group.sync.aligned %0;\n" ::"n"(N) : "memory"); }

#define FENCE_F32(arr, n) _Pragma("unroll") for (int _i = 0; _i < n; _i++) asm volatile("" : "+f"(arr[_i])::"memory")
#define FENCE_U32(arr, n) _Pragma("unroll") for (int _i = 0; _i < n; _i++) asm volatile("" : "+r"(arr[_i])::"memory")

__device__ __forceinline__ uint64_t make_desc(uint32_t addr, uint32_t lbo, uint32_t sbo) {
    return (uint64_t)((addr & 0x3FFFF) >> 4) | ((uint64_t)(lbo >> 4) << 16) | ((uint64_t)(sbo >> 4) << 32);
}

__device__ __forceinline__ void wgmma_m64n32k16_ss(float (&d)[16], uint64_t adesc, uint64_t desc) {
    asm volatile(
        "wgmma.mma_async.sync.aligned.m64n32k16.f32.bf16.bf16 "
        "{%0,%1,%2,%3,%4,%5,%6,%7,%8,%9,%10,%11,%12,%13,%14,%15}, "
        "%16, %17, 1, 1, 1, 0, 0;\n"
        : "+f"(d[0]), "+f"(d[1]), "+f"(d[2]), "+f"(d[3]), "+f"(d[4]), "+f"(d[5]), "+f"(d[6]), "+f"(d[7]), "+f"(d[8]),
          "+f"(d[9]), "+f"(d[10]), "+f"(d[11]), "+f"(d[12]), "+f"(d[13]), "+f"(d[14]), "+f"(d[15])
        : "l"(adesc), "l"(desc));
}
__device__ __forceinline__ void wgmma_m64n32k16_ss0(float (&d)[16], uint64_t adesc, uint64_t desc) {
    asm volatile(
        "{\n.reg .pred p;\nsetp.ne.b32 p, 0, 0;\n"
        "wgmma.mma_async.sync.aligned.m64n32k16.f32.bf16.bf16 "
        "{%0,%1,%2,%3,%4,%5,%6,%7,%8,%9,%10,%11,%12,%13,%14,%15}, "
        "%16, %17, p, 1, 1, 0, 0;\n}\n"
        : "=f"(d[0]), "=f"(d[1]), "=f"(d[2]), "=f"(d[3]), "=f"(d[4]), "=f"(d[5]), "=f"(d[6]), "=f"(d[7]), "=f"(d[8]),
          "=f"(d[9]), "=f"(d[10]), "=f"(d[11]), "=f"(d[12]), "=f"(d[13]), "=f"(d[14]), "=f"(d[15])
        : "l"(adesc), "l"(desc));
}
__device__ __forceinline__ void wgmma_m64n16k16_tb(float (&d)[16], uint64_t adesc, uint64_t desc) {
    asm volatile(
        "wgmma.mma_async.sync.aligned.m64n16k16.f32.bf16.bf16 "
        "{%0,%1,%2,%3,%4,%5,%6,%7}, "
        "%8, %9, 1, 1, 1, 0, 1;\n"
        : "+f"(d[0]), "+f"(d[1]), "+f"(d[2]), "+f"(d[3]), "+f"(d[4]), "+f"(d[5]), "+f"(d[6]), "+f"(d[7])
        : "l"(adesc), "l"(desc));
}
__device__ __forceinline__ void wgmma_m64n64k16_tb(float (&d)[32], uint64_t adesc, uint64_t desc) {
    asm volatile(
        "wgmma.mma_async.sync.aligned.m64n64k16.f32.bf16.bf16 "
        "{%0,%1,%2,%3,%4,%5,%6,%7,%8,%9,%10,%11,%12,%13,%14,%15,%16,%17,%18,%19,%20,%21,%22,%23,%24,%25,%26,%27,%28,%29,%30,%31}, "
        "%32, %33, 1, 1, 1, 0, 1;\n"
        : "+f"(d[0]), "+f"(d[1]), "+f"(d[2]), "+f"(d[3]), "+f"(d[4]), "+f"(d[5]), "+f"(d[6]), "+f"(d[7]), "+f"(d[8]),
          "+f"(d[9]), "+f"(d[10]), "+f"(d[11]), "+f"(d[12]), "+f"(d[13]), "+f"(d[14]), "+f"(d[15]), "+f"(d[16]),
          "+f"(d[17]), "+f"(d[18]), "+f"(d[19]), "+f"(d[20]), "+f"(d[21]), "+f"(d[22]), "+f"(d[23]), "+f"(d[24]),
          "+f"(d[25]), "+f"(d[26]), "+f"(d[27]), "+f"(d[28]), "+f"(d[29]), "+f"(d[30]), "+f"(d[31])
        : "l"(adesc), "l"(desc));
}
__device__ __forceinline__ uint64_t make_desc_sw128(uint32_t addr, uint32_t lbo, uint32_t sbo) {
    return make_desc(addr, lbo, sbo) | (1ull << 62);
}
__device__ __forceinline__ unsigned int ld_acquire(const unsigned int* p) {
    unsigned int v;
    asm volatile("ld.acquire.gpu.global.u32 %0, [%1];\n" : "=r"(v) : "l"(p) : "memory");
    return v;
}
__device__ __forceinline__ void red_release(unsigned int* p) {
    asm volatile("red.release.gpu.global.add.u32 [%0], 1;\n" ::"l"(p) : "memory");
}
__device__ __forceinline__ void spin_until(const unsigned int* p, unsigned int target) {
    for (unsigned int it = 0; ld_acquire(p) < target; it++) {
        if (it > (1u << 24)) __trap();
    }
}
__device__ __forceinline__ void wgmma_m64n32k16(float (&d)[16], uint32_t a0, uint32_t a1, uint32_t a2, uint32_t a3,
                                                uint64_t desc) {
    asm volatile(
        "wgmma.mma_async.sync.aligned.m64n32k16.f32.bf16.bf16 "
        "{%0,%1,%2,%3,%4,%5,%6,%7,%8,%9,%10,%11,%12,%13,%14,%15}, "
        "{%16,%17,%18,%19}, %20, 1, 1, 1, 1;\n"
        : "+f"(d[0]), "+f"(d[1]), "+f"(d[2]), "+f"(d[3]), "+f"(d[4]), "+f"(d[5]), "+f"(d[6]), "+f"(d[7]), "+f"(d[8]),
          "+f"(d[9]), "+f"(d[10]), "+f"(d[11]), "+f"(d[12]), "+f"(d[13]), "+f"(d[14]), "+f"(d[15])
        : "r"(a0), "r"(a1), "r"(a2), "r"(a3), "l"(desc));
}

__device__ __forceinline__ float2 cadd(float2 a, float2 b) { return make_float2(a.x + b.x, a.y + b.y); }
__device__ __forceinline__ float2 csub(float2 a, float2 b) { return make_float2(a.x - b.x, a.y - b.y); }
template <int DIR>
__device__ __forceinline__ float2 cmulw(float2 a, float2 w) {
    if (DIR > 0) return make_float2(fmaf(a.x, w.x, -a.y * w.y), fmaf(a.x, w.y, a.y * w.x));
    else return make_float2(fmaf(a.x, w.x, a.y * w.y), fmaf(a.y, w.x, -a.x * w.y));
}
template <int DIR>
__device__ __forceinline__ float2 rot90(float2 a) {
    if (DIR > 0) return make_float2(a.y, -a.x);
    else return make_float2(-a.y, a.x);
}
template <int DIR>
__device__ __forceinline__ void dft4(float2& a0, float2& a1, float2& a2, float2& a3) {
    float2 t0 = cadd(a0, a2), t1 = csub(a0, a2), t2 = cadd(a1, a3), t3 = rot90<DIR>(csub(a1, a3));
    a0 = cadd(t0, t2); a2 = csub(t0, t2); a1 = cadd(t1, t3); a3 = csub(t1, t3);
}
template <int DIR>
__device__ __forceinline__ void dft8(float2 (&v)[8]) {
    const float h = 0.70710678118654752f;
    dft4<DIR>(v[0], v[2], v[4], v[6]);
    dft4<DIR>(v[1], v[3], v[5], v[7]);
    float2 o1 = v[3], o2 = rot90<DIR>(v[5]), o3 = v[7];
    float2 r1 = rot90<DIR>(o1), r3 = rot90<DIR>(o3);
    o1 = make_float2((o1.x + r1.x) * h, (o1.y + r1.y) * h);
    o3 = make_float2((r3.x - o3.x) * h, (r3.y - o3.y) * h);
    float2 e0 = v[0], e1 = v[2], e2 = v[4], e3 = v[6], o0 = v[1];
    v[0] = cadd(e0, o0); v[4] = csub(e0, o0);
    v[1] = cadd(e1, o1); v[5] = csub(e1, o1);
    v[2] = cadd(e2, o2); v[6] = csub(e2, o2);
    v[3] = cadd(e3, o3); v[7] = csub(e3, o3);
}
template <int DIR>
__device__ __forceinline__ void dft16(float2 (&v)[16]) {
    const float c1 = 0.92387953251128674f, s1 = 0.38268343236508977f, h = 0.70710678118654752f;
#pragma unroll
    for (int n2 = 0; n2 < 4; n2++) dft4<DIR>(v[n2], v[4 + n2], v[8 + n2], v[12 + n2]);
    const float2 w1 = make_float2(c1, -s1), w2 = make_float2(h, -h), w3 = make_float2(s1, -c1);
    const float2 w6 = make_float2(-h, -h), w9 = make_float2(-c1, s1);
    v[4 + 1] = cmulw<DIR>(v[4 + 1], w1);
    v[4 + 2] = cmulw<DIR>(v[4 + 2], w2);
    v[4 + 3] = cmulw<DIR>(v[4 + 3], w3);
    v[8 + 1] = cmulw<DIR>(v[8 + 1], w2);
    v[8 + 2] = rot90<DIR>(v[8 + 2]);
    v[8 + 3] = cmulw<DIR>(v[8 + 3], w6);
    v[12 + 1] = cmulw<DIR>(v[12 + 1], w3);
    v[12 + 2] = cmulw<DIR>(v[12 + 2], w6);
    v[12 + 3] = cmulw<DIR>(v[12 + 3], w9);
#pragma unroll
    for (int k1 = 0; k1 < 4; k1++) dft4<DIR>(v[4 * k1], v[4 * k1 + 1], v[4 * k1 + 2], v[4 * k1 + 3]);
    float2 t;
#define SWP(a, b) t = v[a]; v[a] = v[b]; v[b] = t;
    SWP(1, 4) SWP(2, 8) SWP(3, 12) SWP(6, 9) SWP(7, 13) SWP(11, 14)
#undef SWP
}
template <int DIR>
__device__ __forceinline__ void dft7(float2 (&v)[7]) {
    const float c1 = 0.62348980185873353f, c2 = -0.22252093395631440f, c3 = -0.90096886790241913f;
    const float s1 = 0.78183148246802981f, s2 = 0.97492791218182361f, s3 = 0.43388373911755812f;
    float2 a1 = cadd(v[1], v[6]), b1 = csub(v[1], v[6]);
    float2 a2 = cadd(v[2], v[5]), b2 = csub(v[2], v[5]);
    float2 a3 = cadd(v[3], v[4]), b3 = csub(v[3], v[4]);
    float2 x0 = v[0];
    float2 r1 = make_float2(fmaf(c3, a3.x, fmaf(c2, a2.x, fmaf(c1, a1.x, x0.x))), fmaf(c3, a3.y, fmaf(c2, a2.y, fmaf(c1, a1.y, x0.y))));
    float2 r2 = make_float2(fmaf(c1, a3.x, fmaf(c3, a2.x, fmaf(c2, a1.x, x0.x))), fmaf(c1, a3.y, fmaf(c3, a2.y, fmaf(c2, a1.y, x0.y))));
    float2 r3 = make_float2(fmaf(c2, a3.x, fmaf(c1, a2.x, fmaf(c3, a1.x, x0.x))), fmaf(c2, a3.y, fmaf(c1, a2.y, fmaf(c3, a1.y, x0.y))));
    float2 i1 = make_float2(fmaf(s3, b3.x, fmaf(s2, b2.x, s1 * b1.x)), fmaf(s3, b3.y, fmaf(s2, b2.y, s1 * b1.y)));
    float2 i2 = make_float2(fmaf(-s1, b3.x, fmaf(-s3, b2.x, s2 * b1.x)), fmaf(-s1, b3.y, fmaf(-s3, b2.y, s2 * b1.y)));
    float2 i3 = make_float2(fmaf(s2, b3.x, fmaf(-s1, b2.x, s3 * b1.x)), fmaf(s2, b3.y, fmaf(-s1, b2.y, s3 * b1.y)));
    v[0] = make_float2(x0.x + a1.x + a2.x + a3.x, x0.y + a1.y + a2.y + a3.y);
    i1 = rot90<DIR>(i1); i2 = rot90<DIR>(i2); i3 = rot90<DIR>(i3);
    v[1] = cadd(r1, i1); v[6] = csub(r1, i1);
    v[2] = cadd(r2, i2); v[5] = csub(r2, i2);
    v[3] = cadd(r3, i3); v[4] = csub(r3, i3);
}

#define FFT_SMEM (4 * 2 * 448 * 8)
#define BAR_FFT() asm volatile("bar.sync 6, 128;\n" ::: "memory")

__device__ __forceinline__ float2 cmul(float2 a, float2 b) {
    return make_float2(fmaf(a.x, b.x, -a.y * b.y), fmaf(a.x, b.y, a.y * b.x));
}
template <int DIR, int N>
__device__ __forceinline__ void twiddle(float2 (&v)[N], float2 w1) {
    float2 w2 = cmul(w1, w1), w3 = cmul(w2, w1), w4 = cmul(w2, w2);
    v[1] = cmulw<DIR>(v[1], w1);
    v[2] = cmulw<DIR>(v[2], w2);
    v[3] = cmulw<DIR>(v[3], w3);
    v[4] = cmulw<DIR>(v[4], w4);
    v[5] = cmulw<DIR>(v[5], cmul(w4, w1));
    v[6] = cmulw<DIR>(v[6], cmul(w4, w2));
    if (N > 7) v[7 % N] = cmulw<DIR>(v[7 % N], cmul(w4, w3));
    if (N > 8) {
        float2 w8 = cmul(w4, w4);
        v[8 % N] = cmulw<DIR>(v[8 % N], w8);
        v[9 % N] = cmulw<DIR>(v[9 % N], cmul(w8, w1));
        v[10 % N] = cmulw<DIR>(v[10 % N], cmul(w8, w2));
        v[11 % N] = cmulw<DIR>(v[11 % N], cmul(w8, w3));
        float2 w12 = cmul(w8, w4);
        v[12 % N] = cmulw<DIR>(v[12 % N], w12);
        v[13 % N] = cmulw<DIR>(v[13 % N], cmul(w12, w1));
        v[14 % N] = cmulw<DIR>(v[14 % N], cmul(w12, w2));
        v[15 % N] = cmulw<DIR>(v[15 % N], cmul(w12, w3));
    }
}

__device__ __forceinline__ void fft_row_fwd(float2* bA, int row, int lane, const __nv_bfloat16* __restrict__ x) {
    float2 v0[8], v1[8];
    const int t1 = lane + 32;
    const bool hi = t1 < 56;
    {
        const uint4* src = (const uint4*)(x + (size_t)row * DM);
        uint4 q0 = __ldg(src + lane), q1 = __ldg(src + 32 + lane), q2 = __ldg(src + 64 + lane), q3 = make_uint4(0, 0, 0, 0);
        if (lane < 16) q3 = __ldg(src + 96 + lane);
        float2 wa = __ldg(&TWA448[56 + lane]), wb = __ldg(&TWA448[56 + (hi ? t1 : 0)]);
        uint4* st = (uint4*)bA;
        st[lane] = q0; st[32 + lane] = q1; st[64 + lane] = q2;
        if (lane < 16) st[96 + lane] = q3;
        __syncwarp();
        const __nv_bfloat16* ra = (const __nv_bfloat16*)bA + lane;
#pragma unroll
        for (int n1 = 0; n1 < 8; n1++) v0[n1] = make_float2(__bfloat162float(ra[n1 * 56]), __bfloat162float(ra[DM + n1 * 56]));
        if (hi) {
#pragma unroll
            for (int n1 = 0; n1 < 8; n1++) v1[n1] = make_float2(__bfloat162float(ra[32 + n1 * 56]), __bfloat162float(ra[32 + DM + n1 * 56]));
        }
        __syncwarp();
        dft8<1>(v0);
        twiddle<1, 8>(v0, wa);
#pragma unroll
        for (int k1 = 0; k1 < 8; k1++) bA[k1 * 56 + lane] = v0[k1];
        if (hi) {
            dft8<1>(v1);
            twiddle<1, 8>(v1, wb);
#pragma unroll
            for (int k1 = 0; k1 < 8; k1++) bA[k1 * 56 + t1] = v1[k1];
        }
    }
    __syncwarp();
    {
        const int ka = lane / 7, na = lane - ka * 7, kb = t1 / 7, nb = t1 - kb * 7;
#pragma unroll
        for (int n3 = 0; n3 < 8; n3++) v0[n3] = bA[ka * 56 + n3 * 7 + na];
        if (hi) {
#pragma unroll
            for (int n3 = 0; n3 < 8; n3++) v1[n3] = bA[kb * 56 + n3 * 7 + nb];
        }
        float2 wa = __ldg(&TWB56[7 + na]), wb = __ldg(&TWB56[7 + nb]);
        __syncwarp();
        dft8<1>(v0);
        twiddle<1, 8>(v0, wa);
#pragma unroll
        for (int k2 = 0; k2 < 8; k2++) bA[(ka * 8 + k2) * 7 + na] = v0[k2];
        if (hi) {
            dft8<1>(v1);
            twiddle<1, 8>(v1, wb);
#pragma unroll
            for (int k2 = 0; k2 < 8; k2++) bA[(kb * 8 + k2) * 7 + nb] = v1[k2];
        }
    }
    __syncwarp();
    {
        float2 u0[7], u1[7];
#pragma unroll
        for (int n4 = 0; n4 < 7; n4++) { u0[n4] = bA[lane * 7 + n4]; u1[n4] = bA[t1 * 7 + n4]; }
        __syncwarp();
        dft7<1>(u0);
        dft7<1>(u1);
#pragma unroll
        for (int k3 = 0; k3 < 7; k3++) {
            bA[(lane >> 3) + 8 * (lane & 7) + 64 * k3] = u0[k3];
            bA[(t1 >> 3) + 8 * (t1 & 7) + 64 * k3] = u1[k3];
        }
    }
    __syncwarp();
#pragma unroll
    for (int i = 0; i < 8; i++) {
        const int k = lane + 32 * i;
        if (k < DF) {
            float2 zk = bA[k];
            float2 zm = bA[k == 0 ? 0 : 448 - k];
            float4 o;
            o.x = zk.x + zm.x; o.y = zk.y - zm.y;
            o.z = zk.y + zm.y; o.w = zm.x - zk.x;
            *(float4*)(g_T + (size_t)k * SEQ + row) = o;
        }
    }
    __syncwarp();
}

__device__ __forceinline__ void fft_col(unsigned char* smem, int col, int t) {
    float2* sm = (float2*)smem;
    const unsigned int* sw = (const unsigned int*)(smem + 19456);
#pragma unroll
    for (int i = 0; i < 4; i++) cp_async16(smem_u32(smem) + 19456 + (t + i * 128) * 16, g_Wt + (size_t)col * SEQ + (t + i * 128) * 4);
    cp_async_commit();
    const float scale = 1.0f / (2.0f * 2048.0f * 448.0f);
    float2* T = g_T + (size_t)col * SEQ;
    const int k1 = t >> 3, n4 = t & 7;
    float2 v[16];
#pragma unroll
    for (int i = 0; i < 16; i++) v[i] = __ldcg(&T[i * 128 + t]);
    const float2 wa = __ldg(&TWA2048[128 + t]);
    const float2 wb = __ldg(&TWB128[8 + n4]);
    dft16<1>(v);
    twiddle<1, 16>(v, wa);
#pragma unroll
    for (int k = 0; k < 16; k++) sm[k * 136 + t] = v[k];
    BAR_FFT();
#pragma unroll
    for (int n3 = 0; n3 < 16; n3++) v[n3] = sm[k1 * 136 + n3 * 8 + n4];
    dft16<1>(v);
    twiddle<1, 16>(v, wb);
    BAR_FFT();
#pragma unroll
    for (int k2 = 0; k2 < 16; k2++) sm[k1 * 152 + k2 * 9 + n4] = v[k2];
    cp_async_wait<0>();
    BAR_FFT();
#pragma unroll 1
    for (int h = 0; h < 2; h++) {
        const int k2 = n4 + 8 * h;
        float2 u[8];
#pragma unroll
        for (int i = 0; i < 8; i++) u[i] = sm[k1 * 152 + k2 * 9 + i];
        const float2 wc = __ldg(&TWB128[k2 * 8 + 1]);
        dft8<1>(u);
#pragma unroll
        for (int k3 = 0; k3 < 8; k3++) {
            unsigned int w = sw[k1 + 16 * k2 + 256 * k3];
            float wr = __uint_as_float(w << 16) * scale, wi = __uint_as_float(w & 0xffff0000u) * scale;
            u[k3] = make_float2(fmaf(u[k3].x, wr, -u[k3].y * wi), fmaf(u[k3].x, wi, u[k3].y * wr));
        }
        dft8<-1>(u);
        twiddle<-1, 8>(u, wc);
#pragma unroll
        for (int i = 0; i < 8; i++) sm[k1 * 152 + k2 * 9 + i] = u[i];
    }
    BAR_FFT();
#pragma unroll
    for (int k2 = 0; k2 < 16; k2++) v[k2] = sm[k1 * 152 + k2 * 9 + n4];
    dft16<-1>(v);
    BAR_FFT();
#pragma unroll
    for (int n3 = 0; n3 < 16; n3++) sm[k1 * 136 + n3 * 8 + n4] = v[n3];
    BAR_FFT();
#pragma unroll
    for (int k = 0; k < 16; k++) v[k] = sm[k * 136 + t];
    twiddle<-1, 16>(v, wa);
    dft16<-1>(v);
#pragma unroll
    for (int i = 0; i < 16; i++) T[i * 128 + t] = v[i];
    BAR_FFT();
}

__device__ __forceinline__ void fft_row_inv(float2* bA, int row, int lane, __nv_bfloat16* __restrict__ out) {
    const int t1 = lane + 32;
    const bool hi = t1 < 56;
    float4 yy[8];
#pragma unroll
    for (int i = 0; i < 8; i++) {
        const int k = lane + 32 * i;
        yy[i] = __ldcg((const float4*)(g_T + (size_t)(k < DF ? k : 0) * SEQ + row));
    }
#pragma unroll
    for (int i = 0; i < 8; i++) {
        const int k = lane + 32 * i;
        if (k < DF) {
            float4 y = yy[i];
            if (k == 0 || k == 224) { y.y = 0.f; y.w = 0.f; }
            bA[k] = make_float2(y.x - y.w, y.y + y.z);
            if (k != 0 && k != 224) bA[448 - k] = make_float2(y.x + y.w, y.z - y.y);
        }
    }
    __syncwarp();
    {
        float2 u0[7], u1[7];
#pragma unroll
        for (int k3 = 0; k3 < 7; k3++) {
            u0[k3] = bA[(lane >> 3) + 8 * (lane & 7) + 64 * k3];
            u1[k3] = bA[(t1 >> 3) + 8 * (t1 & 7) + 64 * k3];
        }
        float2 w1 = __ldg(&TWB56[(lane & 7) * 7 + 1]);
        __syncwarp();
        dft7<-1>(u0);
        twiddle<-1, 7>(u0, w1);
        dft7<-1>(u1);
        twiddle<-1, 7>(u1, w1);
#pragma unroll
        for (int n4 = 0; n4 < 7; n4++) { bA[lane * 7 + n4] = u0[n4]; bA[t1 * 7 + n4] = u1[n4]; }
    }
    __syncwarp();
    float2 v0[8], v1[8];
    {
        const int ka = lane / 7, na = lane - ka * 7, kb = t1 / 7, nb = t1 - kb * 7;
#pragma unroll
        for (int k2 = 0; k2 < 8; k2++) v0[k2] = bA[(ka * 8 + k2) * 7 + na];
        if (hi) {
#pragma unroll
            for (int k2 = 0; k2 < 8; k2++) v1[k2] = bA[(kb * 8 + k2) * 7 + nb];
        }
        __syncwarp();
        dft8<-1>(v0);
#pragma unroll
        for (int n3 = 0; n3 < 8; n3++) bA[ka * 56 + n3 * 7 + na] = v0[n3];
        if (hi) {
            dft8<-1>(v1);
#pragma unroll
            for (int n3 = 0; n3 < 8; n3++) bA[kb * 56 + n3 * 7 + nb] = v1[n3];
        }
    }
    __syncwarp();
    {
#pragma unroll
        for (int k1 = 0; k1 < 8; k1++) v0[k1] = bA[k1 * 56 + lane];
        twiddle<-1, 8>(v0, __ldg(&TWA448[56 + lane]));
        dft8<-1>(v0);
        __nv_bfloat16* ra = out + (size_t)row * OUT_LD + DM + lane;
#pragma unroll
        for (int n1 = 0; n1 < 8; n1++) {
            ra[n1 * 56] = __float2bfloat16(v0[n1].x);
            ra[OUT_LD + n1 * 56] = __float2bfloat16(v0[n1].y);
        }
        if (hi) {
#pragma unroll
            for (int k1 = 0; k1 < 8; k1++) v1[k1] = bA[k1 * 56 + t1];
            twiddle<-1, 8>(v1, __ldg(&TWA448[56 + t1]));
            dft8<-1>(v1);
#pragma unroll
            for (int n1 = 0; n1 < 8; n1++) {
                ra[32 + n1 * 56] = __float2bfloat16(v1[n1].x);
                ra[32 + OUT_LD + n1 * 56] = __float2bfloat16(v1[n1].y);
            }
        }
    }
    __syncwarp();
}

#define SM_W 0
#define SM_X 114688
#define SM_Q (SM_X + 65536)
#define SM_FFT (SM_Q + 16384)
#define ATT_SMEM (SM_FFT + FFT_SMEM)
#define NSTAGE 4
#define NTILES 32
#define NSUPER 16

struct SyncState {
    unsigned int kv_flag[NSUPER];
    unsigned int o_flag[32];
    unsigned int fft_bar[2];
    unsigned int done;
};
__device__ SyncState g_sync;

#define BAR_X (bar0 + (2 * NSTAGE) * 8)
#define BAR_WQ(ch) (bar0 + (2 * NSTAGE + 1 + (ch)) * 8)
#define BAR_WO (bar0 + (2 * NSTAGE + 8) * 8)
#define BAR_O (bar0 + (2 * NSTAGE + 9) * 8)
#define BAR_ATT() asm volatile("bar.sync 5, 512;\n" ::: "memory")

#define TR(k)
#define TRP(k)
#define TRF(k)
#define TRK(k)
__device__ __forceinline__ void attn_phase(float (&sx)[16], float (&sy)[16], float (&o)[16], uint32_t (&p)[8], float& R0, float& R1,
                                           uint32_t qext_addr, uint64_t qd, uint64_t kd, uint64_t vd, uint32_t rel_bar, bool do_rel,
                                           bool force) {
    wgmma_fence();
    wgmma_m64n32k16_ss0(sy, qd, kd);
    wgmma_m64n32k16_ss(sy, qd + 16, kd + 16);
    wgmma_commit();
    wgmma_wait<2>();
    FENCE_U32(p, 8);
    if (do_rel) mbar_arrive(rel_bar);
    uint32_t chk = 0;
#pragma unroll
    for (int i = 0; i < 4; i++) {
        p[2 * i] = pack_bf16(ex2(sx[4 * i]), ex2(sx[4 * i + 1]));
        p[2 * i + 1] = pack_bf16(ex2(sx[4 * i + 2]), ex2(sx[4 * i + 3]));
        chk |= p[2 * i] | p[2 * i + 1];
    }
    if (__builtin_expect(__any_sync(0xffffffffu, (chk & 0x40004000u) != 0u) || force, 0)) {
        wgmma_wait<0>();
        FENCE_F32(o, 16);
        FENCE_F32(sy, 16);
        float t0 = fmaxf(sx[0], sx[1]), t1 = fmaxf(sx[2], sx[3]);
#pragma unroll
        for (int i = 1; i < 4; i++) {
            t0 = fmaxf(t0, fmaxf(sx[4 * i], sx[4 * i + 1]));
            t1 = fmaxf(t1, fmaxf(sx[4 * i + 2], sx[4 * i + 3]));
        }
        t0 = fmaxf(t0, __shfl_xor_sync(0xffffffffu, t0, 1));
        t1 = fmaxf(t1, __shfl_xor_sync(0xffffffffu, t1, 1));
        t0 = fmaxf(t0, __shfl_xor_sync(0xffffffffu, t0, 2));
        t1 = fmaxf(t1, __shfl_xor_sync(0xffffffffu, t1, 2));
        float w0 = (force || t0 > -8.f) ? R0 + t0 + 8.f : R0;
        float w1 = (force || t1 > -8.f) ? R1 + t1 + 8.f : R1;
        __nv_bfloat16 h0 = __float2bfloat16(w0), h1 = __float2bfloat16(w1);
        __nv_bfloat16 l0 = __float2bfloat16(w0 - __bfloat162float(h0)), l1 = __float2bfloat16(w1 - __bfloat162float(h1));
        float n0 = __bfloat162float(h0) + __bfloat162float(l0), n1 = __bfloat162float(h1) + __bfloat162float(l1);
        float d0 = n0 - R0, d1 = n1 - R1;
        R0 = n0; R1 = n1;
        if ((threadIdx.x & 3) == 0) {
            uint32_t e0 = ((uint32_t)__bfloat16_as_ushort(h0) | ((uint32_t)__bfloat16_as_ushort(l0) << 16)) ^ 0x80008000u;
            uint32_t e1 = ((uint32_t)__bfloat16_as_ushort(h1) | ((uint32_t)__bfloat16_as_ushort(l1) << 16)) ^ 0x80008000u;
            asm volatile("st.shared.u32 [%0], %1;\n" ::"r"(qext_addr), "r"(e0) : "memory");
            asm volatile("st.shared.u32 [%0], %1;\n" ::"r"(qext_addr + 512), "r"(e1) : "memory");
        }
        asm volatile("fence.proxy.async.shared::cta;\n" ::: "memory");
        __syncwarp();
        float a0 = force ? 0.f : ex2(-d0), a1 = force ? 0.f : ex2(-d1);
#pragma unroll
        for (int i = 0; i < 4; i++) {
            o[4 * i] *= a0; o[4 * i + 1] *= a0;
            o[4 * i + 2] *= a1; o[4 * i + 3] *= a1;
            p[2 * i] = pack_bf16(ex2(sx[4 * i] - d0), ex2(sx[4 * i + 1] - d0));
            p[2 * i + 1] = pack_bf16(ex2(sx[4 * i + 2] - d1), ex2(sx[4 * i + 3] - d1));
            sy[4 * i] -= d0; sy[4 * i + 1] -= d0;
            sy[4 * i + 2] -= d1; sy[4 * i + 3] -= d1;
        }
        FENCE_F32(o, 16);
        FENCE_F32(sy, 16);
    }
    FENCE_U32(p, 8);
    wgmma_fence();
#pragma unroll
    for (int t = 0; t < 2; t++) wgmma_m64n32k16(o, p[4 * t], p[4 * t + 1], p[4 * t + 2], p[4 * t + 3], vd + t * 64);
    wgmma_commit();
    wgmma_wait<1>();
    FENCE_F32(sy, 16);
}

__device__ __forceinline__ void store_o(const float (&o)[16], unsigned char* img, int row, int d0, int lane) {
    float l0 = __shfl_sync(0xffffffffu, o[12], (lane & ~3) | 2);
    float l1 = __shfl_sync(0xffffffffu, o[14], (lane & ~3) | 2);
    float i0 = 1.0f / l0, i1 = 1.0f / l1;
#pragma unroll
    for (int i = 0; i < 4; i++) {
        if (i < 3 || (lane & 3) < 2) {
            int d = d0 + i * 8;
            unsigned char* a = img + (d >> 3) * 1024 + row * 16 + (d & 7) * 2;
            *(uint32_t*)a = pack_bf16(o[4 * i] * i0, o[4 * i + 1] * i0);
            *(uint32_t*)(a + 128) = pack_bf16(o[4 * i + 2] * i1, o[4 * i + 3] * i1);
        }
    }
}

#define W_BLK 57344

__device__ __forceinline__ void grid_barrier(unsigned int* ctr, unsigned int target, int tid) {
    __threadfence();
    BAR_FFT();
    if (tid == 0) {
        atomicAdd(ctr, 1u);
        spin_until(ctr, target);
    }
    BAR_FFT();
}
__device__ __forceinline__ void finish_role() {
    __threadfence();
    if (atomicAdd(&g_sync.done, 1u) == 2 * gridDim.x - 1) {
        for (int i = 0; i < NSUPER; i++) g_sync.kv_flag[i] = 0u;
        for (int i = 0; i < 32; i++) g_sync.o_flag[i] = 0u;
        g_sync.fft_bar[0] = 0u;
        g_sync.fft_bar[1] = 0u;
        g_sync.done = 0u;
        __threadfence();
    }
}

__global__ void __launch_bounds__(640, 1) fused_kernel(const __grid_constant__ CUtensorMap tm_x, const __grid_constant__ CUtensorMap tm_wq,
                                                       const __grid_constant__ CUtensorMap tm_wo,
                                                       const __nv_bfloat16* __restrict__ wk, const __nv_bfloat16* __restrict__ wv,
                                                       const __nv_bfloat16* __restrict__ bx,
                                                       const __nv_bfloat16* __restrict__ w_r, const __nv_bfloat16* __restrict__ w_i,
                                                       __nv_bfloat16* __restrict__ out) {
    extern __shared__ __align__(1024) unsigned char smem[];
    __shared__ __align__(8) uint64_t bars[2 * NSTAGE + 10];
    const uint32_t sb = smem_u32(smem);
    const uint32_t sW = sb + SM_W, sX = sb + SM_X, sKV = sb + SM_X;
    const uint32_t bar0 = smem_u32(bars);
    const int tid = threadIdx.x, warp = tid >> 5, lane = tid & 31;
    const int wg = warp >> 2;
    const int g = blockIdx.x >> 2, c = blockIdx.x & 3;
    const int head = c * 4 + wg;
    if (tid == 0) {
        for (int s = 0; s < NSTAGE; s++) {
            mbar_init(bar0 + s * 8, 1);
            mbar_init(bar0 + (NSTAGE + s) * 8, 16);
        }
        for (int s = 0; s < 10; s++) mbar_init(bar0 + (2 * NSTAGE + s) * 8, 1);
        asm volatile("fence.mbarrier_init.release.cluster;\n" ::: "memory");
        mbar_expect_tx(BAR_X, 57344);
        for (int ch = 0; ch < 7; ch++) tma_2d(sX + ch * 8192, &tm_x, ch * 64, g * 64, BAR_X);
    }
    if (wg == 4) {
        unsigned char* fs = smem + SM_FFT;
        const int ft = tid - 512;
        asm volatile("bar.sync 10, 256;\n" ::: "memory");
#pragma unroll 1
        for (int it = 0; it < 2; it++) fft_row_fwd((float2*)fs + (ft >> 5) * 448, blockIdx.x * 16 + (it * 4 + (ft >> 5)) * 2, lane, bx);
#pragma unroll 4
        for (int i = ft; i < 16 * DF; i += 128) {
            int sr = i & 15, k = i >> 4;
            unsigned int a = __ldg((const unsigned short*)w_r + (size_t)(blockIdx.x * 16 + sr) * DF + k);
            unsigned int b = __ldg((const unsigned short*)w_i + (size_t)(blockIdx.x * 16 + sr) * DF + k);
            g_Wt[(size_t)k * SEQ + blockIdx.x * 16 + sr] = a | (b << 16);
        }
        TRF(0)
        grid_barrier(&g_sync.fft_bar[0], gridDim.x, ft);
        TRF(1)
#pragma unroll 1
        for (int col = blockIdx.x; col < DF; col += 128) fft_col(fs, col, ft);
        TRF(3)
        grid_barrier(&g_sync.fft_bar[1], gridDim.x, ft);
        TRF(4)
#pragma unroll 1
        for (int it = 0; it < 2; it++) fft_row_inv((float2*)fs + (ft >> 5) * 448, blockIdx.x * 16 + (it * 4 + (ft >> 5)) * 2, lane, out);
        TRF(5)
        if (ft == 0) finish_role();
        return;
    }
    if (wg == 2) {
            const __nv_bfloat16* wkv = ((c < 2) ? wk : wv) + (c & 1) * 16;
#pragma unroll 2
            for (int i = 0; i < 14; i++) {
                int idx = tid - 256 + i * 128;
                int q = idx & 3, k = idx >> 2;
                uint32_t dst = sb + SM_Q + (q >> 1) * 7168 + (k >> 3) * 128 + (k & 7) * 16 + (q & 1) * 8;
                if (q < 3 || !(c & 1)) cp_async8(dst, wkv + (size_t)k * DHEAD + q * 4);
                else asm volatile("st.shared.v2.u32 [%0], {%1,%1};\n" ::"r"(dst), "r"(0u) : "memory");
            }
            cp_async_commit();
    }
    BAR_ATT();
    if (tid == 448) {
        for (int ch = 0; ch < 7; ch++) {
            mbar_expect_tx(BAR_WQ(ch), 16384);
            tma_2d(sW + ch * 8192, &tm_wq, c * 112, ch * 64, BAR_WQ(ch));
            tma_2d(sW + W_BLK + ch * 8192, &tm_wq, c * 112 + 64, ch * 64, BAR_WQ(ch));
        }
    }
    __syncwarp();
    TRP(0)
    float acc[32];
#pragma unroll
    for (int i = 0; i < 32; i++) acc[i] = 0.f;
    const uint64_t xdesc = make_desc_sw128(sX, 16, 1024);
    const uint64_t wdesc = make_desc_sw128(sW + (wg & 1) * W_BLK, W_BLK, 1024);
    if (wg < 2) {
        mbar_wait(BAR_X, 0);
#pragma unroll
        for (int ch = 0; ch < 7; ch++) {
            mbar_wait(BAR_WQ(ch), 0);
            if (ch == 0) { TRP(1) }
            FENCE_F32(acc, 32);
            wgmma_fence();
#pragma unroll
            for (int k = 0; k < 4; k++) wgmma_m64n64k16_tb(acc, xdesc + ch * 512 + k * 2, wdesc + (ch * 4 + k) * 128);
            wgmma_commit();
        }
        wgmma_wait<0>();
        FENCE_F32(acc, 32);
        TRP(8)
        asm volatile("bar.arrive 9, 512;\n" ::: "memory");
        asm volatile("bar.sync 8, 384;\n" ::: "memory");
        const float cs = 0.18898223650461362f * 1.4426950408889634f;
        const int rl = (warp & 3) * 16 + (lane >> 2);
#pragma unroll
        for (int j = 0; j < 8; j++) {
            int col = wg * 64 + j * 8 + (lane & 3) * 2;
            if (col < 112) {
                int hh = col / 28, d = col - hh * 28;
                uint32_t a = sb + SM_Q + hh * 4096 + (rl >> 3) * 512 + (d >> 3) * 128 + (rl & 7) * 16 + (d & 7) * 2;
                asm volatile("st.shared.u32 [%0], %1;\n" ::"r"(a), "r"(pack_bf16(acc[4 * j] * cs, acc[4 * j + 1] * cs)) : "memory");
                asm volatile("st.shared.u32 [%0], %1;\n" ::"r"(a + 512), "r"(pack_bf16(acc[4 * j + 2] * cs, acc[4 * j + 3] * cs)) : "memory");
            }
        }
        asm volatile("st.shared.v2.u32 [%0], {%1,%1};\n" ::"r"(sb + SM_Q + (tid >> 6) * 4096 + ((tid & 63) >> 3) * 512 + 384 + (tid & 7) * 16 + 8), "r"(0u) : "memory");
    } else if (wg == 3) {
        if (warp == 12 && lane < NSUPER) spin_until(&g_sync.kv_flag[lane], 32u);
        __syncwarp();
        asm volatile("bar.sync 9, 512;\n" ::: "memory");
        if (lane == 0) {
            const int st = warp & 3;
            mbar_expect_tx(bar0 + st * 8, 16384);
            bulk_g2s(sKV + st * 16384, g_KV + ((st + blockIdx.x) & (NSUPER - 1)) * 16384, 16384, bar0 + st * 8);
        }
        __syncwarp();
    } else {
        {
            cp_async_wait<0>();
            asm volatile("fence.proxy.async.shared::cta;\n" ::: "memory");
            asm volatile("bar.sync 4, 128;\n" ::: "memory");
            TRK(0)
            mbar_wait(BAR_X, 0);
            TRK(1)
        }
        float kv[16];
#pragma unroll
        for (int i = 0; i < 16; i++) kv[i] = 0.f;
        const uint64_t kvdesc = make_desc(sb + SM_Q, 128, 7168);
        FENCE_F32(kv, 8);
        wgmma_fence();
#pragma unroll
        for (int ch = 0; ch < 7; ch++) {
#pragma unroll
            for (int k = 0; k < 4; k++) wgmma_m64n16k16_tb(kv, xdesc + ch * 512 + k * 2, kvdesc + (ch * 4 + k) * 16);
        }
        wgmma_commit();
        wgmma_wait<0>();
        FENCE_F32(kv, 8);
        TRK(2)
        asm volatile("bar.arrive 8, 384;\n" ::: "memory");
        asm volatile("bar.arrive 9, 512;\n" ::: "memory");
        const int rl = g * 64 + (warp & 3) * 16 + (lane >> 2);
        unsigned char* img = g_KV + (rl >> 7) * 16384 + (c >> 1) * 8192 + ((rl & 127) >> 3) * 512 + (rl & 7) * 16;
#pragma unroll
        for (int j = 0; j < 2; j++) {
            int d = (c & 1) * 16 + j * 8 + (lane & 3) * 2;
#pragma unroll
            for (int h = 0; h < 2; h++) {
                float v0 = kv[4 * j + 2 * h], v1 = kv[4 * j + 2 * h + 1];
                if (d == 28) { v0 = 1.0f; if (c < 2) v1 = 1.0f; }
                *(uint32_t*)(img + h * 512 + (d >> 3) * 128 + (d & 7) * 2) = pack_bf16(v0, v1);
            }
        }
        TRK(3)
        asm volatile("fence.proxy.async.global;\n" ::: "memory");
        __syncwarp();
        if (lane == 0) red_release(&g_sync.kv_flag[g >> 1]);
        TRK(5)
        asm volatile("bar.arrive 10, 256;\n" ::: "memory");
    }
    asm volatile("fence.proxy.async.shared::cta;\n" ::: "memory");
    BAR_ATT();
    TRP(9)
    __syncwarp();
    TRP(10)
    TRP(11)
    const uint32_t sQ = sb + SM_Q + wg * 4096;
    const uint64_t qdesc = make_desc(sQ, 128, 512);
    float o[16], sa[16], sb2[16];
    uint32_t pa[8], pb[8];
#pragma unroll
    for (int i = 0; i < 16; i++) o[i] = 0.f;
#pragma unroll
    for (int i = 0; i < 8; i++) { pa[i] = 0u; pb[i] = 0u; }
    float R0 = 0.f, R1 = 0.f;
    const uint32_t qext = sQ + ((warp & 3) * 2) * 512 + 3 * 128 + (lane >> 2) * 16 + 8;
    const uint64_t kdesc = make_desc(sKV, 128, 512);
    const uint64_t vdesc = make_desc(sKV + 8192, 512, 128);
    mbar_wait(bar0, 0);
    FENCE_F32(o, 16);
    wgmma_fence();
    wgmma_m64n32k16_ss0(sa, qdesc, kdesc);
    wgmma_m64n32k16_ss(sa, qdesc + 16, kdesc + 16);
    wgmma_commit();
    wgmma_wait<0>();
    FENCE_F32(sa, 16);
    TRP(13)
#pragma unroll 1
    for (int T = 0; T < NSUPER; T++) {
        const int cst = T & (NSTAGE - 1);
        const int pst = (T - 1) & (NSTAGE - 1);
        const int Tn = (T + 1 < NSUPER) ? T + 1 : T;
        const int nst = Tn & (NSTAGE - 1);
        const uint64_t kc = kdesc + cst * 1024, vc = vdesc + cst * 1024;
        if (T == 1 && tid == 288) {
            mbar_expect_tx(BAR_WO, 114688);
            for (int ch = 0; ch < 7; ch++) {
                tma_2d(sW + ch * 8192, &tm_wo, c * 112, ch * 64, BAR_WO);
                tma_2d(sW + W_BLK + ch * 8192, &tm_wo, c * 112 + 64, ch * 64, BAR_WO);
            }
        }
        if (T >= 2 && T + 2 < NSUPER && (T & 3) == wg && (warp & 3) == 0) {
            if (lane == 0) {
                const int rs = (T - 2) & (NSTAGE - 1);
                mbar_wait(bar0 + (NSTAGE + rs) * 8, ((T - 2) >> 2) & 1);
                mbar_expect_tx(bar0 + rs * 8, 16384);
                bulk_g2s(sKV + rs * 16384, g_KV + ((T + 2 + blockIdx.x) & (NSUPER - 1)) * 16384, 16384, bar0 + rs * 8);
            }
        }
        __syncwarp();
        attn_phase(sa, sb2, o, pa, R0, R1, qext, qdesc, kc + 128, vc, 0, false, T == 0);
        attn_phase(sb2, sa, o, pb, R0, R1, qext, qdesc, kc + 256, vc + 128, bar0 + (NSTAGE + pst) * 8, lane == 0 && T > 0, false);
        attn_phase(sa, sb2, o, pa, R0, R1, qext, qdesc, kc + 384, vc + 256, 0, false, false);
        mbar_wait(bar0 + nst * 8, (Tn / NSTAGE) & 1);
        attn_phase(sb2, sa, o, pb, R0, R1, qext, qdesc, kdesc + nst * 1024, vc + 384, 0, false, false);
    }
    wgmma_wait<0>();
    FENCE_F32(o, 16);
    store_o(o, (unsigned char*)g_O + (size_t)g * 57344, (warp & 3) * 16 + (lane >> 2), head * DHEAD + (lane & 3) * 2, lane);
    TRP(12)
    __syncwarp();
    if (lane == 0) red_release(&g_sync.o_flag[g]);
    if (tid == 384) {
        spin_until(&g_sync.o_flag[g], 64u);
        asm volatile("fence.proxy.async.global;\n" ::: "memory");
        mbar_expect_tx(BAR_O, 57344);
        bulk_g2s(sX, (const unsigned char*)g_O + (size_t)g * 57344, 57344, BAR_O);
    }
    __syncwarp();
    TRP(14)
    TRP(15)
    if (wg < 2) {
#pragma unroll
        for (int i = 0; i < 32; i++) acc[i] = 0.f;
        const uint64_t odesc = make_desc(sX, 1024, 128);
        mbar_wait(BAR_WO, 0);
        mbar_wait(BAR_O, 0);
        TRP(2)
        FENCE_F32(acc, 32);
        wgmma_fence();
#pragma unroll
        for (int k = 0; k < 28; k++) wgmma_m64n64k16_tb(acc, odesc + k * 128, wdesc + k * 128);
        wgmma_commit();
        wgmma_wait<0>();
        FENCE_F32(acc, 32);
        TRP(3)
        const uint32_t stg = sb + SM_Q + ((warp & 3) * 16 + (lane >> 2)) * 240 + (wg * 64 + (lane & 3) * 2) * 2;
#pragma unroll
        for (int j = 0; j < 8; j++) {
            if (wg * 64 + j * 8 < 112) {
                asm volatile("st.shared.u32 [%0], %1;\n" ::"r"(stg + j * 16), "r"(pack_bf16(acc[4 * j], acc[4 * j + 1])) : "memory");
                asm volatile("st.shared.u32 [%0], %1;\n" ::"r"(stg + j * 16 + 8 * 240), "r"(pack_bf16(acc[4 * j + 2], acc[4 * j + 3])) : "memory");
            }
        }
        asm volatile("bar.sync 7, 256;\n" ::: "memory");
#pragma unroll
        for (int i = 0; i < 4; i++) {
            int idx = tid + i * 256;
            int r = idx >> 4, ch = idx & 15;
            if (ch < 14) {
                uint4 v;
                asm volatile("ld.shared.v4.u32 {%0,%1,%2,%3}, [%4];\n" : "=r"(v.x), "=r"(v.y), "=r"(v.z), "=r"(v.w) : "r"(sb + SM_Q + r * 240 + ch * 16));
                *(uint4*)(out + (size_t)(g * 64 + r) * OUT_LD + c * 112 + ch * 8) = v;
            }
        }
    }
    BAR_ATT();
    if (tid == 0) finish_role();
}

typedef CUresult (*PFN_encodeTiled)(CUtensorMap*, CUtensorMapDataType, cuuint32_t, void*, const cuuint64_t*, const cuuint64_t*,
                                    const cuuint32_t*, const cuuint32_t*, CUtensorMapInterleave, CUtensorMapSwizzle,
                                    CUtensorMapL2promotion, CUtensorMapFloatOOBfill);
static void make_map(PFN_encodeTiled enc, CUtensorMap* m, const void* ptr, int rows) {
    cuuint64_t dims[2] = {(cuuint64_t)DM, (cuuint64_t)rows};
    cuuint64_t strides[1] = {(cuuint64_t)DM * 2};
    cuuint32_t box[2] = {64, 64};
    cuuint32_t estr[2] = {1, 1};
    enc(m, CU_TENSOR_MAP_DATA_TYPE_BFLOAT16, 2, (void*)ptr, dims, strides, box, estr, CU_TENSOR_MAP_INTERLEAVE_NONE,
        CU_TENSOR_MAP_SWIZZLE_128B, CU_TENSOR_MAP_L2_PROMOTION_L2_128B, CU_TENSOR_MAP_FLOAT_OOB_FILL_NONE);
}

extern "C" void kernel_launch(void* const* d_in, const int* in_sizes, int n_in, void* d_out, int out_size) {
    static PFN_encodeTiled enc = nullptr;
    if (!enc) {
        cudaFuncSetAttribute(fused_kernel, cudaFuncAttributeMaxDynamicSharedMemorySize, ATT_SMEM);
        void* fn = nullptr;
        cudaDriverEntryPointQueryResult qres;
        cudaGetDriverEntryPoint("cuTensorMapEncodeTiled", &fn, cudaEnableDefault, &qres);
        enc = (PFN_encodeTiled)fn;
    }
    CUtensorMap tm_x, tm_wq, tm_wo;
    make_map(enc, &tm_x, d_in[0], SEQ);
    make_map(enc, &tm_wq, d_in[1], DM);
    make_map(enc, &tm_wo, d_in[4], DM);
    fused_kernel<<<128, 640, ATT_SMEM, cudaStreamPerThread>>>(
        tm_x, tm_wq, tm_wo, (const __nv_bfloat16*)d_in[2], (const __nv_bfloat16*)d_in[3], (const __nv_bfloat16*)d_in[5],
        (const __nv_bfloat16*)d_in[6], (const __nv_bfloat16*)d_in[7], (__nv_bfloat16*)d_out);
}
```
